```python
import torch

def _softmax(x, axis=-1):
    return torch.softmax(x, dim=axis)

def _gelu(x):
    return torch.nn.functional.gelu(x, approximate='tanh')

def _silu(x):
    return torch.nn.functional.silu(x)

def _sigmoid(x):
    return torch.sigmoid(x)

def _layernorm(x, axis=-1, eps=1e-05):
    m = x.mean(dim=axis, keepdim=True)
    v = x.var(dim=axis, keepdim=True, unbiased=False)
    return (x - m) / torch.sqrt(v + eps)

def _scatter_add(tgt, idx, src, axis=0):
    return tgt.clone().index_add_(axis, idx, src)

def _segment_sum(src, seg, n):
    out = torch.zeros((n,) + src.shape[1:], dtype=src.dtype)
    return out.index_add_(0, seg, src)

def _pad(x, pw):
    flat = tuple((v for pair in reversed(pw) for v in pair))
    return torch.nn.functional.pad(x, flat)
kernel_name = 'adaLN_cond__spectral_gfnet__glu_gated_swiglu__prompt'

def setup_inputs():

    _w = lambda a: (lambda t: t.to(torch.bfloat16) if t.is_floating_point() else t)(torch.as_tensor(a))

    def _A_setup():
        B, S, D = (1, 2048, 512)
        Df = D // 2 + 1
        return {'x': _w((lambda *s: torch.randn(*s, dtype=torch.bfloat16) * 0.05)(B, S, D)), 'w_r': _w((lambda *s: torch.randn(*s, dtype=torch.bfloat16) * 3.2)(S, Df) * 0.02), 'w_i': _w((lambda *s: torch.randn(*s, dtype=torch.bfloat16) * 3.2)(S, Df) * 0.02)}
    _A_in = _A_setup()

    def _B_setup():
        B, S, D, F = (1, 2048, 512, 1376)
        return {'x': _w((lambda *s: torch.randn(*s, dtype=torch.bfloat16) * 0.05)(B, S, D)), 'w1': _w((lambda *s: torch.randn(*s, dtype=torch.bfloat16) * 0.4)(D, F) * (2.0 / D) ** 0.5), 'w3': _w((lambda *s: torch.randn(*s, dtype=torch.bfloat16) * 0.4)(D, F) * (2.0 / D) ** 0.5), 'w2': _w((lambda *s: torch.randn(*s, dtype=torch.bfloat16) * 0.4)(F, D) * (2.0 / F) ** 0.5)}
    _B_in = _B_setup()
    return {'A_x': _A_in['x'], 'A_w_r': _A_in['w_r'], 'A_w_i': _A_in['w_i'], 'B_x': _B_in['x'], 'B_w1': _B_in['w1'], 'B_w3': _B_in['w3'], 'B_w2': _B_in['w2'], 'c': _w((lambda *s: torch.randn(*s, dtype=torch.bfloat16) * 0.1)(1, 512) * 8.0), 'w_mod': _w((lambda *s: torch.randn(*s, dtype=torch.bfloat16) * 0.1)(512, 6 * 512) * 512 ** (-0.5) * 8.0)}

def reference(A_x, A_w_r, A_w_i, B_x, B_w1, B_w3, B_w2, c, w_mod):

    def _A_ref(x, w_r, w_i):
        B, S, D = x.shape
        X = (lambda x, axes=(-2, -1): torch.fft.rfft2(x.float(), dim=axes))(x, axes=(-2, -1))
        W = w_r + 1j * w_i
        X = X * W
        y = (lambda x, s, axes=(-2, -1): torch.fft.irfft2(x, s=s, dim=axes).to(torch.bfloat16))(X, (S, D), axes=(-2, -1))
        return y

    def _B_ref(x, w1, w3, w2):
        gate = torch.einsum('bsd,df->bsf', x, w1)
        up = torch.einsum('bsd,df->bsf', x, w3)
        h = _silu(gate) * up
        out = torch.einsum('bsf,fd->bsd', h, w2)
        return out
    x = A_x
    mod = (_silu(c) @ w_mod).reshape(c.shape[0], 6, 1, -1)
    sa, ca, ga, sb, cb, gb = (mod[:, 0].clone(), mod[:, 1].clone(), mod[:, 2].clone(), mod[:, 3].clone(), mod[:, 4].clone(), mod[:, 5].clone())
    h = _layernorm(x, axis=-1) * (1 + ca) + sa
    x = x + ga * _A_ref(h, A_w_r, A_w_i)
    h = _layernorm(x, axis=-1) * (1 + cb) + sb
    x = x + gb * _B_ref(h, B_w1, B_w3, B_w2)
    return x
```

```cpp
#include <cuda_runtime.h>
#include <cuda.h>
#include <cuda_bf16.h>
#include <stdint.h>

__device__ __align__(128) const uint32_t g_tbl[17792] = {
0x3e800000,0x3e800000,0x3e800000,0xbe800000,0x3e800000,0x3e800000,0x3e800000,0xbe800000,0x3e800000,0x3e800000,0x3e800000,0xbe800000,0x3e800000,0x3e800000,0x3e800000,0xbe800000,
0x3e800000,0x3e6c835e,0x0,0xbdc3ef15,0x3e3504f3,0x3dc3ef15,0xbe3504f3,0xbe6c835e,0x0,0xbdc3ef15,0xbe800000,0xbe6c835e,0xbe3504f3,0xbe6c835e,0xbe3504f3,0xbdc3ef15,
0x3e800000,0x3e3504f3,0x0,0xbe3504f3,0x0,0xbe3504f3,0xbe800000,0xbe3504f3,0xbe800000,0xbe3504f3,0x0,0x3e3504f3,0x0,0x3e3504f3,0x3e800000,0x3e3504f3,
0x3e800000,0x3dc3ef15,0x0,0xbe6c835e,0xbe3504f3,0xbe6c835e,0xbe3504f3,0x3dc3ef15,0x0,0x3e6c835e,0x3e800000,0x3dc3ef15,0x3e3504f3,0xbdc3ef15,0xbe3504f3,0xbe6c835e,
0x3e800000,0x0,0x0,0xbe800000,0xbe800000,0x0,0x0,0x3e800000,0x3e800000,0x0,0x0,0xbe800000,0xbe800000,0x0,0x0,0x3e800000,
0x3e800000,0xbdc3ef15,0x0,0xbe6c835e,0xbe3504f3,0x3e6c835e,0x3e3504f3,0x3dc3ef15,0x0,0xbe6c835e,0xbe800000,0x3dc3ef15,0x3e3504f3,0x3dc3ef15,0x3e3504f3,0xbe6c835e,
0x3e800000,0xbe3504f3,0x0,0xbe3504f3,0x0,0x3e3504f3,0x3e800000,0xbe3504f3,0xbe800000,0x3e3504f3,0x0,0x3e3504f3,0x0,0xbe3504f3,0xbe800000,0x3e3504f3,
0x3e800000,0xbe6c835e,0x0,0xbdc3ef15,0x3e3504f3,0xbdc3ef15,0x3e3504f3,0xbe6c835e,0x0,0x3dc3ef15,0x3e800000,0xbe6c835e,0xbe3504f3,0x3e6c835e,0x3e3504f3,0xbdc3ef15,
0x3e800000,0x3e800000,0x3e800000,0xbe800000,0x3e800000,0x3e800000,0x3e800000,0xbe800000,0x3e800000,0x3e800000,0x3e800000,0xbe800000,0x3e800000,0x3e800000,0x3e800000,0xbe800000,
0xbe800000,0xbe6c835e,0x0,0x3dc3ef15,0xbe3504f3,0xbdc3ef15,0x3e3504f3,0x3e6c835e,0x0,0x3dc3ef15,0x3e800000,0x3e6c835e,0x3e3504f3,0x3e6c835e,0x3e3504f3,0x3dc3ef15,
0x3e800000,0x3e3504f3,0x0,0xbe3504f3,0x0,0xbe3504f3,0xbe800000,0xbe3504f3,0xbe800000,0xbe3504f3,0x0,0x3e3504f3,0x0,0x3e3504f3,0x3e800000,0x3e3504f3,
0xbe800000,0xbdc3ef15,0x0,0x3e6c835e,0x3e3504f3,0x3e6c835e,0x3e3504f3,0xbdc3ef15,0x0,0xbe6c835e,0xbe800000,0xbdc3ef15,0xbe3504f3,0x3dc3ef15,0x3e3504f3,0x3e6c835e,
0x3e800000,0x0,0x0,0xbe800000,0xbe800000,0x0,0x0,0x3e800000,0x3e800000,0x0,0x0,0xbe800000,0xbe800000,0x0,0x0,0x3e800000,
0xbe800000,0x3dc3ef15,0x0,0x3e6c835e,0x3e3504f3,0xbe6c835e,0xbe3504f3,0xbdc3ef15,0x0,0x3e6c835e,0x3e800000,0xbdc3ef15,0xbe3504f3,0xbdc3ef15,0xbe3504f3,0x3e6c835e,
0x3e800000,0xbe3504f3,0x0,0xbe3504f3,0x0,0x3e3504f3,0x3e800000,0xbe3504f3,0xbe800000,0x3e3504f3,0x0,0x3e3504f3,0x0,0xbe3504f3,0xbe800000,0x3e3504f3,
0xbe800000,0x3e6c835e,0x0,0x3dc3ef15,0xbe3504f3,0x3dc3ef15,0xbe3504f3,0x3e6c835e,0x0,0xbdc3ef15,0xbe800000,0x3e6c835e,0x3e3504f3,0xbe6c835e,0xbe3504f3,0x3dc3ef15,
0x0,0x0,0x0,0x0,0x0,0x0,0x0,0x0,0x0,0x0,0x0,0x0,0x0,0x0,0x0,0x0,
0x2e1f0000,0xae1f0000,0xae1f0000,0x2e1f0000,0x336431a8,0xb36431a8,0xb364b1a8,0x3364b1a8,0x33643400,0xb3643400,0xb364b400,0x3364b400,0x2e1f31a8,0xae1f31a8,0xae1fb1a8,0x2e1fb1a8,
0x31a80000,0xb1a80000,0x31a80000,0xb1a80000,0x31a83400,0xb1a83400,0x31a83400,0xb1a83400,0xb1a80000,0x31a80000,0xb1a80000,0x31a80000,0xb1a8b400,0x31a8b400,0xb1a8b400,0x31a8b400,
0x33640000,0xb3640000,0xb3640000,0x33640000,0xae1f31a8,0x2e1f31a8,0x2e1fb1a8,0xae1fb1a8,0xae1fb400,0x2e1fb400,0x2e1f3400,0xae1f3400,0x336431a8,0xb36431a8,0xb364b1a8,0x3364b1a8,
0x34000000,0xb4000000,0x34000000,0xb4000000,0xb4000000,0x34000000,0xb4000000,0x34000000,0x34000000,0xb4000000,0x34000000,0xb4000000,0xb4000000,0x34000000,0xb4000000,0x34000000,
0x33640000,0xb3640000,0xb3640000,0x33640000,0xae1fb1a8,0x2e1fb1a8,0x2e1f31a8,0xae1f31a8,0xae1f3400,0x2e1f3400,0x2e1fb400,0xae1fb400,0x3364b1a8,0xb364b1a8,0xb36431a8,0x336431a8,
0x31a80000,0xb1a80000,0x31a80000,0xb1a80000,0x31a8b400,0xb1a8b400,0x31a8b400,0xb1a8b400,0xb1a80000,0x31a80000,0xb1a80000,0x31a80000,0xb1a83400,0x31a83400,0xb1a83400,0x31a83400,
0x2e1f0000,0xae1f0000,0xae1f0000,0x2e1f0000,0x3364b1a8,0xb364b1a8,0xb36431a8,0x336431a8,0x3364b400,0xb364b400,0xb3643400,0x33643400,0x2e1fb1a8,0xae1fb1a8,0xae1f31a8,0x2e1f31a8,
0x34003400,0xb4003400,0x34003400,0xb4003400,0x34003400,0xb4003400,0x34003400,0xb4003400,0x34003400,0xb4003400,0x34003400,0xb4003400,0x34003400,0xb4003400,0x34003400,0xb4003400,
0x33643400,0xb3643400,0xb364b400,0x3364b400,0x2e1f31a8,0xae1f31a8,0xae1fb1a8,0x2e1fb1a8,0xae1f0000,0x2e1f0000,0x2e1f0000,0xae1f0000,0xb364b1a8,0x3364b1a8,0x336431a8,0xb36431a8,
0x31a83400,0xb1a83400,0x31a83400,0xb1a83400,0xb1a80000,0x31a80000,0xb1a80000,0x31a80000,0xb1a8b400,0x31a8b400,0xb1a8b400,0x31a8b400,0x31a80000,0xb1a80000,0x31a80000,0xb1a80000,
0x2e1f3400,0xae1f3400,0xae1fb400,0x2e1fb400,0xb364b1a8,0x3364b1a8,0x336431a8,0xb36431a8,0x33640000,0xb3640000,0xb3640000,0x33640000,0xae1f31a8,0x2e1f31a8,0x2e1fb1a8,0xae1fb1a8,
0x3400,0x3400,0x3400,0x3400,0xb400,0xb400,0xb400,0xb400,0x3400,0x3400,0x3400,0x3400,0xb400,0xb400,0xb400,0xb400,
0xae1f3400,0x2e1f3400,0x2e1fb400,0xae1fb400,0x3364b1a8,0xb364b1a8,0xb36431a8,0x336431a8,0xb3640000,0x33640000,0x33640000,0xb3640000,0x2e1f31a8,0xae1f31a8,0xae1fb1a8,0x2e1fb1a8,
0xb1a83400,0x31a83400,0xb1a83400,0x31a83400,0x31a80000,0xb1a80000,0x31a80000,0xb1a80000,0x31a8b400,0xb1a8b400,0x31a8b400,0xb1a8b400,0xb1a80000,0x31a80000,0xb1a80000,0x31a80000,
0xb3643400,0x33643400,0x3364b400,0xb364b400,0xae1f31a8,0x2e1f31a8,0x2e1fb1a8,0xae1fb1a8,0x2e1f0000,0xae1f0000,0xae1f0000,0x2e1f0000,0x3364b1a8,0xb364b1a8,0xb36431a8,0x336431a8,
0x0,0x0,0x0,0x0,0x0,0x0,0x0,0x0,0x0,0x0,0x0,0x0,0x0,0x0,0x0,0x0,
0xae1f0000,0x2e1f0000,0x2e1f0000,0xae1f0000,0xb364b1a8,0x3364b1a8,0x336431a8,0xb36431a8,0xb364b400,0x3364b400,0x33643400,0xb3643400,0xae1fb1a8,0x2e1fb1a8,0x2e1f31a8,0xae1f31a8,
0xb1a80000,0x31a80000,0xb1a80000,0x31a80000,0xb1a8b400,0x31a8b400,0xb1a8b400,0x31a8b400,0x31a80000,0xb1a80000,0x31a80000,0xb1a80000,0x31a83400,0xb1a83400,0x31a83400,0xb1a83400,
0xb3640000,0x33640000,0x33640000,0xb3640000,0x2e1fb1a8,0xae1fb1a8,0xae1f31a8,0x2e1f31a8,0x2e1f3400,0xae1f3400,0xae1fb400,0x2e1fb400,0xb364b1a8,0x3364b1a8,0x336431a8,0xb36431a8,
0xb4000000,0x34000000,0xb4000000,0x34000000,0x34000000,0xb4000000,0x34000000,0xb4000000,0xb4000000,0x34000000,0xb4000000,0x34000000,0x34000000,0xb4000000,0x34000000,0xb4000000,
0xb3640000,0x33640000,0x33640000,0xb3640000,0x2e1f31a8,0xae1f31a8,0xae1fb1a8,0x2e1fb1a8,0x2e1fb400,0xae1fb400,0xae1f3400,0x2e1f3400,0xb36431a8,0x336431a8,0x3364b1a8,0xb364b1a8,
0xb1a80000,0x31a80000,0xb1a80000,0x31a80000,0xb1a83400,0x31a83400,0xb1a83400,0x31a83400,0x31a80000,0xb1a80000,0x31a80000,0xb1a80000,0x31a8b400,0xb1a8b400,0x31a8b400,0xb1a8b400,
0xae1f0000,0x2e1f0000,0x2e1f0000,0xae1f0000,0xb36431a8,0x336431a8,0x3364b1a8,0xb364b1a8,0xb3643400,0x33643400,0x3364b400,0xb364b400,0xae1f31a8,0x2e1f31a8,0x2e1fb1a8,0xae1fb1a8,
0x0,0xb4003400,0x0,0xb4003400,0x0,0xb4003400,0x0,0xb4003400,0x0,0xb4003400,0x0,0xb4003400,0x0,0xb4003400,0x0,0xb4003400,
0x30722a3e,0xb2a733d9,0xb072aa3e,0x32a7b3d9,0x33d932a7,0xaa3e3072,0xb3d9b2a7,0x2a3eb072,0x32a733d9,0x3072aa3e,0xb2a7b3d9,0xb0722a3e,0x2a3e3072,0x33d9b2a7,0xaa3eb072,0xb3d932a7,
0x33642e1f,0xae1f3364,0x33642e1f,0xae1f3364,0x2e1f3364,0x3364ae1f,0x2e1f3364,0x3364ae1f,0xb364ae1f,0x2e1fb364,0xb364ae1f,0x2e1fb364,0xae1fb364,0xb3642e1f,0xae1fb364,0xb3642e1f,
0x33d93072,0x2a3e32a7,0xb3d9b072,0xaa3eb2a7,0xb2a72a3e,0x3072b3d9,0x32a7aa3e,0xb07233d9,0x2a3eb2a7,0xb3d93072,0xaa3e32a7,0x33d9b072,0x307233d9,0x32a72a3e,0xb072b3d9,0xb2a7aa3e,
0x31a831a8,0x31a831a8,0x31a831a8,0x31a831a8,0xb1a8b1a8,0xb1a8b1a8,0xb1a8b1a8,0xb1a8b1a8,0x31a831a8,0x31a831a8,0x31a831a8,0x31a831a8,0xb1a8b1a8,0xb1a8b1a8,0xb1a8b1a8,0xb1a8b1a8,
0x2a3e32a7,0x33d93072,0xaa3eb2a7,0xb3d9b072,0x3072b3d9,0xb2a72a3e,0xb07233d9,0x32a7aa3e,0xb3d93072,0x2a3eb2a7,0x33d9b072,0xaa3e32a7,0x32a72a3e,0x307233d9,0xb2a7aa3e,0xb072b3d9,
0xae1f3364,0x33642e1f,0xae1f3364,0x33642e1f,0x3364ae1f,0x2e1f3364,0x3364ae1f,0x2e1f3364,0x2e1fb364,0xb364ae1f,0x2e1fb364,0xb364ae1f,0xb3642e1f,0xae1fb364,0xb3642e1f,0xae1fb364,
0xb2a733d9,0x30722a3e,0x32a7b3d9,0xb072aa3e,0xaa3e3072,0x33d932a7,0x2a3eb072,0xb3d9b2a7,0x3072aa3e,0x32a733d9,0xb0722a3e,0xb2a7b3d9,0x33d9b2a7,0x2a3e3072,0xb3d932a7,0xaa3eb072,
0x34003400,0x0,0x34003400,0x0,0x34003400,0x0,0x34003400,0x0,0x34003400,0x0,0x34003400,0x0,0x34003400,0x0,0x34003400,0x0,
0x32a733d9,0x3072aa3e,0xb2a7b3d9,0xb0722a3e,0x2a3e3072,0x33d9b2a7,0xaa3eb072,0xb3d932a7,0xb072aa3e,0x32a7b3d9,0x30722a3e,0xb2a733d9,0xb3d9b2a7,0x2a3eb072,0x33d932a7,0xaa3e3072,
0x2e1f3364,0x3364ae1f,0x2e1f3364,0x3364ae1f,0xb364ae1f,0x2e1fb364,0xb364ae1f,0x2e1fb364,0xae1fb364,0xb3642e1f,0xae1fb364,0xb3642e1f,0x33642e1f,0xae1f3364,0x33642e1f,0xae1f3364,
0xaa3e32a7,0x33d9b072,0x2a3eb2a7,0xb3d93072,0xb072b3d9,0xb2a7aa3e,0x307233d9,0x32a72a3e,0x33d93072,0x2a3e32a7,0xb3d9b072,0xaa3eb2a7,0xb2a72a3e,0x3072b3d9,0x32a7aa3e,0xb07233d9,
0xb1a831a8,0x31a8b1a8,0xb1a831a8,0x31a8b1a8,0x31a8b1a8,0xb1a831a8,0x31a8b1a8,0xb1a831a8,0xb1a831a8,0x31a8b1a8,0xb1a831a8,0x31a8b1a8,0x31a8b1a8,0xb1a831a8,0x31a8b1a8,0xb1a831a8,
0xb3d93072,0x2a3eb2a7,0x33d9b072,0xaa3e32a7,0x32a72a3e,0x307233d9,0xb2a7aa3e,0xb072b3d9,0xaa3eb2a7,0xb3d9b072,0x2a3e32a7,0x33d93072,0xb07233d9,0x32a7aa3e,0x3072b3d9,0xb2a72a3e,
0xb3642e1f,0xae1fb364,0xb3642e1f,0xae1fb364,0xae1f3364,0x33642e1f,0xae1f3364,0x33642e1f,0x3364ae1f,0x2e1f3364,0x3364ae1f,0x2e1f3364,0x2e1fb364,0xb364ae1f,0x2e1fb364,0xb364ae1f,
0xb0722a3e,0xb2a7b3d9,0x3072aa3e,0x32a733d9,0xb3d932a7,0xaa3eb072,0x33d9b2a7,0x2a3e3072,0xb2a733d9,0x30722a3e,0x32a7b3d9,0xb072aa3e,0xaa3e3072,0x33d932a7,0x2a3eb072,0xb3d9b2a7,
0x0,0x3400b400,0x0,0x3400b400,0x0,0x3400b400,0x0,0x3400b400,0x0,0x3400b400,0x0,0x3400b400,0x0,0x3400b400,0x0,0x3400b400,
0xb072aa3e,0x32a7b3d9,0x30722a3e,0xb2a733d9,0xb3d9b2a7,0x2a3eb072,0x33d932a7,0xaa3e3072,0xb2a7b3d9,0xb0722a3e,0x32a733d9,0x3072aa3e,0xaa3eb072,0xb3d932a7,0x2a3e3072,0x33d9b2a7,
0xb364ae1f,0x2e1fb364,0xb364ae1f,0x2e1fb364,0xae1fb364,0xb3642e1f,0xae1fb364,0xb3642e1f,0x33642e1f,0xae1f3364,0x33642e1f,0xae1f3364,0x2e1f3364,0x3364ae1f,0x2e1f3364,0x3364ae1f,
0xb3d9b072,0xaa3eb2a7,0x33d93072,0x2a3e32a7,0x32a7aa3e,0xb07233d9,0xb2a72a3e,0x3072b3d9,0xaa3e32a7,0x33d9b072,0x2a3eb2a7,0xb3d93072,0xb072b3d9,0xb2a7aa3e,0x307233d9,0x32a72a3e,
0xb1a8b1a8,0xb1a8b1a8,0xb1a8b1a8,0xb1a8b1a8,0x31a831a8,0x31a831a8,0x31a831a8,0x31a831a8,0xb1a8b1a8,0xb1a8b1a8,0xb1a8b1a8,0xb1a8b1a8,0x31a831a8,0x31a831a8,0x31a831a8,0x31a831a8,
0xaa3eb2a7,0xb3d9b072,0x2a3e32a7,0x33d93072,0xb07233d9,0x32a7aa3e,0x3072b3d9,0xb2a72a3e,0x33d9b072,0xaa3e32a7,0xb3d93072,0x2a3eb2a7,0xb2a7aa3e,0xb072b3d9,0x32a72a3e,0x307233d9,
0x2e1fb364,0xb364ae1f,0x2e1fb364,0xb364ae1f,0xb3642e1f,0xae1fb364,0xb3642e1f,0xae1fb364,0xae1f3364,0x33642e1f,0xae1f3364,0x33642e1f,0x3364ae1f,0x2e1f3364,0x3364ae1f,0x2e1f3364,
0x32a7b3d9,0xb072aa3e,0xb2a733d9,0x30722a3e,0x2a3eb072,0xb3d9b2a7,0xaa3e3072,0x33d932a7,0xb0722a3e,0xb2a7b3d9,0x3072aa3e,0x32a733d9,0xb3d932a7,0xaa3eb072,0x33d9b2a7,0x2a3e3072,
0x34003400,0x34003400,0x0,0x0,0x34003400,0x34003400,0x0,0x0,0x34003400,0x34003400,0x0,0x0,0x34003400,0x34003400,0x0,0x0,
0x0,0x0,0x34003400,0x34003400,0x0,0x0,0x34003400,0x34003400,0x0,0x0,0x34003400,0x34003400,0x0,0x0,0x34003400,0x34003400,
0x31a83400,0x31a83400,0x31a80000,0x31a80000,0xb1a80000,0xb1a80000,0x31a83400,0x31a83400,0xb1a8b400,0xb1a8b400,0xb1a80000,0xb1a80000,0x31a80000,0x31a80000,0xb1a8b400,0xb1a8b400,
0xb1a80000,0xb1a80000,0x31a83400,0x31a83400,0xb1a8b400,0xb1a8b400,0xb1a80000,0xb1a80000,0x31a80000,0x31a80000,0xb1a8b400,0xb1a8b400,0x31a83400,0x31a83400,0x31a80000,0x31a80000,
0x3400,0x3400,0x34000000,0x34000000,0xb400,0xb400,0xb4000000,0xb4000000,0x3400,0x3400,0x34000000,0x34000000,0xb400,0xb400,0xb4000000,0xb4000000,
0xb4000000,0xb4000000,0x3400,0x3400,0x34000000,0x34000000,0xb400,0xb400,0xb4000000,0xb4000000,0x3400,0x3400,0x34000000,0x34000000,0xb400,0xb400,
0xb1a83400,0xb1a83400,0x31a80000,0x31a80000,0x31a80000,0x31a80000,0x31a8b400,0x31a8b400,0x31a8b400,0x31a8b400,0xb1a80000,0xb1a80000,0xb1a80000,0xb1a80000,0xb1a83400,0xb1a83400,
0xb1a80000,0xb1a80000,0xb1a83400,0xb1a83400,0xb1a83400,0xb1a83400,0x31a80000,0x31a80000,0x31a80000,0x31a80000,0x31a8b400,0x31a8b400,0x31a8b400,0x31a8b400,0xb1a80000,0xb1a80000,
0x33643400,0xb364b400,0x2e1f0000,0xae1f0000,0x2e1f31a8,0xae1fb1a8,0x336431a8,0xb364b1a8,0xae1f0000,0x2e1f0000,0x33643400,0xb364b400,0xb364b1a8,0x336431a8,0x2e1f31a8,0xae1fb1a8,
0xae1f0000,0x2e1f0000,0x33643400,0xb364b400,0xb364b1a8,0x336431a8,0x2e1f31a8,0xae1fb1a8,0xb364b400,0x33643400,0xae1f0000,0x2e1f0000,0xae1fb1a8,0x2e1f31a8,0xb364b1a8,0x336431a8,
0x2e1f3400,0xae1fb400,0x33640000,0xb3640000,0xb364b1a8,0x336431a8,0xae1f31a8,0x2e1fb1a8,0x33640000,0xb3640000,0xae1fb400,0x2e1f3400,0xae1f31a8,0x2e1fb1a8,0x336431a8,0xb364b1a8,
0xb3640000,0x33640000,0x2e1f3400,0xae1fb400,0x2e1fb1a8,0xae1f31a8,0xb364b1a8,0x336431a8,0x2e1f3400,0xae1fb400,0x33640000,0xb3640000,0xb364b1a8,0x336431a8,0xae1f31a8,0x2e1fb1a8,
0xae1f3400,0x2e1fb400,0x33640000,0xb3640000,0x3364b1a8,0xb36431a8,0xae1fb1a8,0x2e1f31a8,0xb3640000,0x33640000,0xae1f3400,0x2e1fb400,0x2e1f31a8,0xae1fb1a8,0x3364b1a8,0xb36431a8,
0xb3640000,0x33640000,0xae1f3400,0x2e1fb400,0x2e1f31a8,0xae1fb1a8,0x3364b1a8,0xb36431a8,0x2e1fb400,0xae1f3400,0xb3640000,0x33640000,0xb36431a8,0x3364b1a8,0x2e1f31a8,0xae1fb1a8,
0xb3643400,0x3364b400,0x2e1f0000,0xae1f0000,0xae1f31a8,0x2e1fb1a8,0x3364b1a8,0xb36431a8,0x2e1f0000,0xae1f0000,0x3364b400,0xb3643400,0x3364b1a8,0xb36431a8,0x2e1fb1a8,0xae1f31a8,
0xae1f0000,0x2e1f0000,0xb3643400,0x3364b400,0xb36431a8,0x3364b1a8,0xae1f31a8,0x2e1fb1a8,0xb3643400,0x3364b400,0x2e1f0000,0xae1f0000,0xae1f31a8,0x2e1fb1a8,0x3364b1a8,0xb36431a8,
0xb4003400,0xb4003400,0x0,0x0,0xb4003400,0xb4003400,0x0,0x0,0xb4003400,0xb4003400,0x0,0x0,0xb4003400,0xb4003400,0x0,0x0,
0x0,0x0,0xb4003400,0xb4003400,0x0,0x0,0xb4003400,0xb4003400,0x0,0x0,0xb4003400,0xb4003400,0x0,0x0,0xb4003400,0xb4003400,
0xb1a83400,0xb1a83400,0xb1a80000,0xb1a80000,0x31a80000,0x31a80000,0xb1a83400,0xb1a83400,0x31a8b400,0x31a8b400,0x31a80000,0x31a80000,0xb1a80000,0xb1a80000,0x31a8b400,0x31a8b400,
0x31a80000,0x31a80000,0xb1a83400,0xb1a83400,0x31a8b400,0x31a8b400,0x31a80000,0x31a80000,0xb1a80000,0xb1a80000,0x31a8b400,0x31a8b400,0xb1a83400,0xb1a83400,0xb1a80000,0xb1a80000,
0x3400,0x3400,0xb4000000,0xb4000000,0xb400,0xb400,0x34000000,0x34000000,0x3400,0x3400,0xb4000000,0xb4000000,0xb400,0xb400,0x34000000,0x34000000,
0x34000000,0x34000000,0x3400,0x3400,0xb4000000,0xb4000000,0xb400,0xb400,0x34000000,0x34000000,0x3400,0x3400,0xb4000000,0xb4000000,0xb400,0xb400,
0x31a83400,0x31a83400,0xb1a80000,0xb1a80000,0xb1a80000,0xb1a80000,0xb1a8b400,0xb1a8b400,0xb1a8b400,0xb1a8b400,0x31a80000,0x31a80000,0x31a80000,0x31a80000,0x31a83400,0x31a83400,
0x31a80000,0x31a80000,0x31a83400,0x31a83400,0x31a83400,0x31a83400,0xb1a80000,0xb1a80000,0xb1a80000,0xb1a80000,0xb1a8b400,0xb1a8b400,0xb1a8b400,0xb1a8b400,0x31a80000,0x31a80000,
0xb3643400,0x3364b400,0xae1f0000,0x2e1f0000,0xae1f31a8,0x2e1fb1a8,0xb36431a8,0x3364b1a8,0x2e1f0000,0xae1f0000,0xb3643400,0x3364b400,0x3364b1a8,0xb36431a8,0xae1f31a8,0x2e1fb1a8,
0x2e1f0000,0xae1f0000,0xb3643400,0x3364b400,0x3364b1a8,0xb36431a8,0xae1f31a8,0x2e1fb1a8,0x3364b400,0xb3643400,0x2e1f0000,0xae1f0000,0x2e1fb1a8,0xae1f31a8,0x3364b1a8,0xb36431a8,
0xae1f3400,0x2e1fb400,0xb3640000,0x33640000,0x3364b1a8,0xb36431a8,0x2e1f31a8,0xae1fb1a8,0xb3640000,0x33640000,0x2e1fb400,0xae1f3400,0x2e1f31a8,0xae1fb1a8,0xb36431a8,0x3364b1a8,
0x33640000,0xb3640000,0xae1f3400,0x2e1fb400,0xae1fb1a8,0x2e1f31a8,0x3364b1a8,0xb36431a8,0xae1f3400,0x2e1fb400,0xb3640000,0x33640000,0x3364b1a8,0xb36431a8,0x2e1f31a8,0xae1fb1a8,
0x2e1f3400,0xae1fb400,0xb3640000,0x33640000,0xb364b1a8,0x336431a8,0x2e1fb1a8,0xae1f31a8,0x33640000,0xb3640000,0x2e1f3400,0xae1fb400,0xae1f31a8,0x2e1fb1a8,0xb364b1a8,0x336431a8,
0x33640000,0xb3640000,0x2e1f3400,0xae1fb400,0xae1f31a8,0x2e1fb1a8,0xb364b1a8,0x336431a8,0xae1fb400,0x2e1f3400,0x33640000,0xb3640000,0x336431a8,0xb364b1a8,0xae1f31a8,0x2e1fb1a8,
0x33643400,0xb364b400,0xae1f0000,0x2e1f0000,0x2e1f31a8,0xae1fb1a8,0xb364b1a8,0x336431a8,0xae1f0000,0x2e1f0000,0xb364b400,0x33643400,0xb364b1a8,0x336431a8,0xae1fb1a8,0x2e1f31a8,
0x2e1f0000,0xae1f0000,0x33643400,0xb364b400,0x336431a8,0xb364b1a8,0x2e1f31a8,0xae1fb1a8,0x33643400,0xb364b400,0xae1f0000,0x2e1f0000,0x2e1f31a8,0xae1fb1a8,0xb364b1a8,0x336431a8,
0x39a839a8,0x39a139a8,0x39a839a8,0x372d3800,0x39a839a8,0x396a398c,0x39a839a8,0x35553649,0x39a839a8,0x38fd393a,0x39a839a8,0x32923454,0x39a839a8,0x385f38b4,0x39a839a8,0x2c70306a,
0x39a839a8,0x399f39a8,0x399f39a1,0x362b372d,0x39a739a8,0x39593985,0x399b399d,0x33e23516,0x39a539a6,0x38d1391d,0x39963998,0x2e17317f,0x39a339a4,0x380c3876,0x39903993,0xabc42471,
0x39a839a8,0x399d39a8,0x3985398c,0x35163649,0x39a439a6,0x3947397d,0x3974397d,0x30f5339f,0x399d39a1,0x38a038fd,0x395f396a,0xa4712c70,0x39933998,0x37643831,0x39473954,0xb209aea4,
0x39a739a8,0x399b39a8,0x3959396a,0x33e23555,0x399f39a4,0x39333974,0x39333947,0x2bc430f5,0x39903998,0x386b38da,0x3905391d,0xb024a871,0x39783985,0x36a137cd,0x38d138ec,0xb4f6b319,
0x39a639a8,0x399839a8,0x391d393a,0x317f3454,0x399839a1,0x391d396a,0x38da38fd,0xa8712c70,0x397d398c,0x383138b4,0x388b38b4,0xb39fb06a,0x3954396a,0x35d1372d,0x3831385f,0xb6bdb555,
0x39a539a8,0x399639a8,0x38d138fd,0x2e173292,0x3990399d,0x3905395f,0x386b38a0,0xb024a471,0x3965397d,0x37e7388b,0x37e73831,0xb575b39f,0x39253947,0x34f63684,0x36da3764,0xb825b6f6,
0x39a439a8,0x399339a8,0x387638b4,0x2471306a,0x39853998,0x38ec3954,0x37cd3831,0xb319aea4,0x3947396a,0x3764385f,0x3684372d,0xb6f6b555,0x38ec391d,0x341235d1,0x351635d1,0xb8c7b831,
0x39a339a8,0x399039a8,0x380c385f,0xabc42c70,0x39783993,0x38d13947,0x36a13764,0xb4f6b209,0x39253954,0x36da3831,0x34f635d1,0xb825b6bd,0x38aa38ec,0x324d3516,0x324d3412,0xb941b8c7,
0x0,0x2c700000,0x0,0x385f3800,0x0,0x3292306a,0x0,0x38fd38b4,0x0,0x35553454,0x0,0x396a393a,0x0,0x372d3649,0x0,0x39a1398c,
0x20710000,0x2cfd0000,0x2cfd2c70,0x38be385f,0x26aa2471,0x335c30f5,0x2e172d8a,0x394d390e,0x298d2871,0x35ef34d6,0x2f302ea4,0x399b397d,0x2bc42aa9,0x37e736f6,0x30242fbd,0x39a339a8,
0x24710000,0x2d8a0000,0x30f5306a,0x390e38b4,0x2aa92871,0x3412317f,0x3209317f,0x39853954,0x2d8a2c70,0x36843555,0x33193292,0x39a839a1,0x2fbd2ea4,0x38493799,0x3412339f,0x39743998,
0x26aa0000,0x2e170000,0x335c3292,0x394d38fd,0x2cfd2aa9,0x34753209,0x34753412,0x39a33985,0x30242ea4,0x371235d1,0x353634d6,0x399039a6,0x31c430f5,0x38963819,0x35ef3594,0x3915395f,
0x28710000,0x2ea40000,0x34d63454,0x397d393a,0x2ea42c70,0x34d63292,0x35d13555,0x39a639a1,0x317f306a,0x37993649,0x36bd3649,0x3954398c,0x339f3292,0x38da385f,0x3799372d,0x388b38fd,
0x298d0000,0x2f300000,0x35ef3555,0x399b396a,0x30242d8a,0x35363319,0x37123684,0x399039a8,0x32d5317f,0x380c36bd,0x380c3799,0x38f53954,0x34b63412,0x391538a0,0x38803849,0x37b33876,
0x2aa90000,0x2fbd0000,0x36f63649,0x39a8398c,0x30f52ea4,0x3594339f,0x38193799,0x395f3998,0x34123292,0x3849372d,0x38a0385f,0x387638fd,0x359434d6,0x394738da,0x390e38da,0x360e3799,
0x2bc40000,0x30240000,0x37e7372d,0x39a339a1,0x31c42fbd,0x35ef3412,0x38963849,0x39153974,0x34b6339f,0x38803799,0x391538da,0x37b3388b,0x36673594,0x396f390e,0x396f3947,0x3433360e,
0x398c39a8,0x396a39a8,0xb06a0000,0xb8fdb800,0x38b4393a,0x372d38b4,0xb649b454,0xb9a1b98c,0x36493800,0x2c703454,0xb8b4b800,0xb85fb93a,0x306a3454,0xb555b06a,0xb98cb93a,0xb292b649,
0x398939a8,0x396539a8,0xb2d5ac70,0xb941b85f,0x3896392c,0x36da38a0,0xb77fb594,0xb981b9a4,0x35b23799,0x26aa339f,0xb925b88b,0xb77fb8da,0x2cfd3319,0xb62bb209,0xb9a8b985,0xacfdb496,
0x398539a8,0x395f39a8,0xb496b06a,0xb974b8b4,0x3876391d,0x3684388b,0xb849b6bd,0xb947b9a6,0x3516372d,0xa4713292,0xb974b8fd,0xb60eb85f,0x2471317f,0xb6f6b39f,0xb993b9a6,0x2aa9b17f,
0x398139a8,0x395939a8,0xb5b2b292,0xb996b8fd,0x3854390e,0x362b3876,0xb8beb7cd,0xb8f5b993,0x347536bd,0xabc4317f,0xb99fb954,0xb475b799,0xa98d2fbd,0xb7b3b496,0xb94db99d,0x31c4aaa9,
0x397d39a8,0x395439a8,0xb6bdb454,0xb9a6b93a,0x383138fd,0x35d1385f,0xb91db85f,0xb88bb96a,0x339f3649,0xaea4306a,0xb9a6b98c,0xb17fb649,0xaea42c70,0xb831b555,0xb8dab96a,0x34d62c70,
0x397839a8,0x394d39a8,0xb7b3b555,0xb9a5b96a,0x380c38ec,0x35753849,0xb965b8c7,0xb80cb92c,0x324d35d1,0xb0b02ea4,0xb989b9a6,0xabc4b4d6,0xb13a2471,0xb880b60e,0xb83db90e,0x36a13209,
0x397439a8,0x394739a8,0xb849b649,0xb993b98c,0x37cd38da,0x35163831,0xb993b91d,0xb6f6b8da,0x30f53555,0xb2092c70,0xb947b9a1,0x2aa9b292,0xb319a871,0xb8c7b6bd,0xb6f6b88b,0x381934d6,
0x396f39a8,0x394139a8,0xb8aab72d,0xb96fb9a1,0x377f38c7,0x34b63819,0xb9a7b95f,0xb5b2b876,0x2f3034d6,0xb35c2871,0xb8e3b97d,0x313aaea4,0xb475ad8a,0xb905b764,0xb536b7cd,0x38be3684,
0x306a0000,0x32920000,0x398c39a8,0x35553800,0x36493454,0x385f3649,0x38b4393a,0xac70306a,0x38b43800,0x39a1393a,0x36493800,0xb72db454,0x398c393a,0x38fd398c,0x306a3454,0xb96ab8b4,
0x30b00000,0x32d50000,0x396539a1,0x3433372d,0x36a13496,0x38803684,0x383d38ec,0xb13a2aa9,0x38e33831,0x39a73954,0x34b636bd,0xb83db5d1,0x399f395f,0x38be3974,0x207130f5,0xb99fb92c,
0x30f50000,0x33190000,0x392c398c,0x32093649,0x36f634d6,0x38a036bd,0x3764388b,0xb412a871,0x390e385f,0x39a8396a,0x32093555,0xb8c7b72d,0x39a8397d,0x38763954,0xafbd2871,0xb9a4b97d,
0x313a0000,0x335c0000,0x38e3396a,0x2f303555,0x37493516,0x38be36f6,0x362b3819,0xb575afbd,0x3933388b,0x39a3397d,0x2cfd339f,0xb933b831,0x39a53993,0x3825392c,0xb3e2ad8a,0xb978b9a4,
0x317f0000,0x339f0000,0x388b393a,0x28713454,0x37993555,0x38da372d,0x34d6372d,0xb6bdb292,0x395438b4,0x3998398c,0xa871306a,0xb97db8b4,0x399839a1,0x379938fd,0xb5d1b292,0xb91db9a1,
0x31c40000,0x33e20000,0x382538fd,0xa98d3292,0x37e73594,0x38f53764,0x32d5360e,0xb7e7b496,0x396f38da,0x39893998,0xb0b02871,0xb9a3b91d,0x398139a8,0x36da38c7,0xb77fb516,0xb896b974,
0x32090000,0x34120000,0x376438b4,0xafbd306a,0x381935d1,0x390e3799,0x2fbd34d6,0xb876b5d1,0x398538fd,0x397439a1,0xb412ac70,0xb9a4b96a,0x395f39a6,0x360e388b,0xb876b6bd,0xb7cdb91d,
0x324d0000,0x34330000,0x3667385f,0xb24d2c70,0x383d360e,0x392537cd,0x26aa3319,0xb8e3b6f6,0x3996391d,0x395939a6,0xb5b2b17f,0xb981b998,0x3933399d,0x35363849,0xb905b819,0xb62bb8a0,
0x3400,0x34000000,0x3400,0x34000000,0x3400,0x34000000,0x3400,0x34000000,0x3400,0x34000000,0x3400,0x34000000,0x3400,0x34000000,0x3400,0x34000000,
0x3400,0x34000000,0xae1f3364,0x33642e1f,0xb1a831a8,0x31a831a8,0xb3642e1f,0x2e1f3364,0xb4000000,0x3400,0xb364ae1f,0xae1f3364,0xb1a8b1a8,0xb1a831a8,0xae1fb364,0xb3642e1f,
0x3400,0x34000000,0xb1a831a8,0x31a831a8,0xb4000000,0x3400,0xb1a8b1a8,0xb1a831a8,0xb400,0xb4000000,0x31a8b1a8,0xb1a8b1a8,0x34000000,0xb400,0x31a831a8,0x31a8b1a8,
0x3400,0x34000000,0xb3642e1f,0x2e1f3364,0xb1a8b1a8,0xb1a831a8,0x2e1fb364,0xb364ae1f,0x34000000,0xb400,0x2e1f3364,0x3364ae1f,0xb1a831a8,0x31a831a8,0xb364ae1f,0xae1f3364,
0x3400,0x34000000,0xb4000000,0x3400,0xb400,0xb4000000,0x34000000,0xb400,0x3400,0x34000000,0xb4000000,0x3400,0xb400,0xb4000000,0x34000000,0xb400,
0x3400,0x34000000,0xb364ae1f,0xae1f3364,0x31a8b1a8,0xb1a8b1a8,0x2e1f3364,0x3364ae1f,0xb4000000,0x3400,0x2e1fb364,0xb364ae1f,0x31a831a8,0x31a8b1a8,0xb3642e1f,0x2e1f3364,
0x3400,0x34000000,0xb1a8b1a8,0xb1a831a8,0x34000000,0xb400,0xb1a831a8,0x31a831a8,0xb400,0xb4000000,0x31a831a8,0x31a8b1a8,0xb4000000,0x3400,0x31a8b1a8,0xb1a8b1a8,
0x3400,0x34000000,0xae1fb364,0xb3642e1f,0x31a831a8,0x31a8b1a8,0xb364ae1f,0xae1f3364,0x34000000,0xb400,0xb3642e1f,0x2e1f3364,0x31a8b1a8,0xb1a8b1a8,0xae1f3364,0x33642e1f,
0x3400,0x34000000,0x3400,0x34000000,0x3400,0x34000000,0x3400,0x34000000,0x3400,0x34000000,0x3400,0x34000000,0x3400,0x34000000,0x3400,0x34000000,
0xb400,0xb4000000,0x2e1fb364,0xb364ae1f,0x31a8b1a8,0xb1a8b1a8,0x3364ae1f,0xae1fb364,0x34000000,0xb400,0x33642e1f,0x2e1fb364,0x31a831a8,0x31a8b1a8,0x2e1f3364,0x3364ae1f,
0x3400,0x34000000,0xb1a831a8,0x31a831a8,0xb4000000,0x3400,0xb1a8b1a8,0xb1a831a8,0xb400,0xb4000000,0x31a8b1a8,0xb1a8b1a8,0x34000000,0xb400,0x31a831a8,0x31a8b1a8,
0xb400,0xb4000000,0x3364ae1f,0xae1fb364,0x31a831a8,0x31a8b1a8,0xae1f3364,0x33642e1f,0xb4000000,0x3400,0xae1fb364,0xb3642e1f,0x31a8b1a8,0xb1a8b1a8,0x33642e1f,0x2e1fb364,
0x3400,0x34000000,0xb4000000,0x3400,0xb400,0xb4000000,0x34000000,0xb400,0x3400,0x34000000,0xb4000000,0x3400,0xb400,0xb4000000,0x34000000,0xb400,
0xb400,0xb4000000,0x33642e1f,0x2e1fb364,0xb1a831a8,0x31a831a8,0xae1fb364,0xb3642e1f,0x34000000,0xb400,0xae1f3364,0x33642e1f,0xb1a8b1a8,0xb1a831a8,0x3364ae1f,0xae1fb364,
0x3400,0x34000000,0xb1a8b1a8,0xb1a831a8,0x34000000,0xb400,0xb1a831a8,0x31a831a8,0xb400,0xb4000000,0x31a831a8,0x31a8b1a8,0xb4000000,0x3400,0x31a8b1a8,0xb1a8b1a8,
0xb400,0xb4000000,0x2e1f3364,0x3364ae1f,0xb1a8b1a8,0xb1a831a8,0x33642e1f,0x2e1fb364,0xb4000000,0x3400,0x3364ae1f,0xae1fb364,0xb1a831a8,0x31a831a8,0x2e1fb364,0xb364ae1f,
0x3400,0x34000000,0xb400,0xb4000000,0x3400,0x34000000,0xb400,0xb4000000,0x3400,0x34000000,0xb400,0xb4000000,0x3400,0x34000000,0xb400,0xb4000000,
0x3400,0x34000000,0x2e1fb364,0xb364ae1f,0xb1a831a8,0x31a831a8,0x3364ae1f,0xae1fb364,0xb4000000,0x3400,0x33642e1f,0x2e1fb364,0xb1a8b1a8,0xb1a831a8,0x2e1f3364,0x3364ae1f,
0x3400,0x34000000,0x31a8b1a8,0xb1a8b1a8,0xb4000000,0x3400,0x31a831a8,0x31a8b1a8,0xb400,0xb4000000,0xb1a831a8,0x31a831a8,0x34000000,0xb400,0xb1a8b1a8,0xb1a831a8,
0x3400,0x34000000,0x3364ae1f,0xae1fb364,0xb1a8b1a8,0xb1a831a8,0xae1f3364,0x33642e1f,0x34000000,0xb400,0xae1fb364,0xb3642e1f,0xb1a831a8,0x31a831a8,0x33642e1f,0x2e1fb364,
0x3400,0x34000000,0x34000000,0xb400,0xb400,0xb4000000,0xb4000000,0x3400,0x3400,0x34000000,0x34000000,0xb400,0xb400,0xb4000000,0xb4000000,0x3400,
0x3400,0x34000000,0x33642e1f,0x2e1fb364,0x31a8b1a8,0xb1a8b1a8,0xae1fb364,0xb3642e1f,0xb4000000,0x3400,0xae1f3364,0x33642e1f,0x31a831a8,0x31a8b1a8,0x3364ae1f,0xae1fb364,
0x3400,0x34000000,0x31a831a8,0x31a8b1a8,0x34000000,0xb400,0x31a8b1a8,0xb1a8b1a8,0xb400,0xb4000000,0xb1a8b1a8,0xb1a831a8,0xb4000000,0x3400,0xb1a831a8,0x31a831a8,
0x3400,0x34000000,0x2e1f3364,0x3364ae1f,0x31a831a8,0x31a8b1a8,0x33642e1f,0x2e1fb364,0x34000000,0xb400,0x3364ae1f,0xae1fb364,0x31a8b1a8,0xb1a8b1a8,0x2e1fb364,0xb364ae1f,
0x3400,0x34000000,0xb400,0xb4000000,0x3400,0x34000000,0xb400,0xb4000000,0x3400,0x34000000,0xb400,0xb4000000,0x3400,0x34000000,0xb400,0xb4000000,
0xb400,0xb4000000,0xae1f3364,0x33642e1f,0x31a8b1a8,0xb1a8b1a8,0xb3642e1f,0x2e1f3364,0x34000000,0xb400,0xb364ae1f,0xae1f3364,0x31a831a8,0x31a8b1a8,0xae1fb364,0xb3642e1f,
0x3400,0x34000000,0x31a8b1a8,0xb1a8b1a8,0xb4000000,0x3400,0x31a831a8,0x31a8b1a8,0xb400,0xb4000000,0xb1a831a8,0x31a831a8,0x34000000,0xb400,0xb1a8b1a8,0xb1a831a8,
0xb400,0xb4000000,0xb3642e1f,0x2e1f3364,0x31a831a8,0x31a8b1a8,0x2e1fb364,0xb364ae1f,0xb4000000,0x3400,0x2e1f3364,0x3364ae1f,0x31a8b1a8,0xb1a8b1a8,0xb364ae1f,0xae1f3364,
0x3400,0x34000000,0x34000000,0xb400,0xb400,0xb4000000,0xb4000000,0x3400,0x3400,0x34000000,0x34000000,0xb400,0xb400,0xb4000000,0xb4000000,0x3400,
0xb400,0xb4000000,0xb364ae1f,0xae1f3364,0xb1a831a8,0x31a831a8,0x2e1f3364,0x3364ae1f,0x34000000,0xb400,0x2e1fb364,0xb364ae1f,0xb1a8b1a8,0xb1a831a8,0xb3642e1f,0x2e1f3364,
0x3400,0x34000000,0x31a831a8,0x31a8b1a8,0x34000000,0xb400,0x31a8b1a8,0xb1a8b1a8,0xb400,0xb4000000,0xb1a8b1a8,0xb1a831a8,0xb4000000,0x3400,0xb1a831a8,0x31a831a8,
0xb400,0xb4000000,0xae1fb364,0xb3642e1f,0xb1a8b1a8,0xb1a831a8,0xb364ae1f,0xae1f3364,0xb4000000,0x3400,0xb3642e1f,0x2e1f3364,0xb1a831a8,0x31a831a8,0xae1f3364,0x33642e1f,
0x39a839a8,0x39a139a8,0x39a839a8,0x372d3800,0x39a839a8,0x396a398c,0x39a839a8,0x35553649,0x39a839a8,0x38fd393a,0x39a839a8,0x32923454,0x39a839a8,0x385f38b4,0x39a839a8,0x2c70306a,
0x39a839a8,0x399f39a8,0x399f39a1,0x362b372d,0x39a739a8,0x39593985,0x399b399d,0x33e23516,0x39a539a6,0x38d1391d,0x39963998,0x2e17317f,0x39a339a4,0x380c3876,0x39903993,0xabc42471,
0x39a839a8,0x399d39a8,0x3985398c,0x35163649,0x39a439a6,0x3947397d,0x3974397d,0x30f5339f,0x399d39a1,0x38a038fd,0x395f396a,0xa4712c70,0x39933998,0x37643831,0x39473954,0xb209aea4,
0x39a739a8,0x399b39a8,0x3959396a,0x33e23555,0x399f39a4,0x39333974,0x39333947,0x2bc430f5,0x39903998,0x386b38da,0x3905391d,0xb024a871,0x39783985,0x36a137cd,0x38d138ec,0xb4f6b319,
0x39a639a8,0x399839a8,0x391d393a,0x317f3454,0x399839a1,0x391d396a,0x38da38fd,0xa8712c70,0x397d398c,0x383138b4,0x388b38b4,0xb39fb06a,0x3954396a,0x35d1372d,0x3831385f,0xb6bdb555,
0x39a539a8,0x399639a8,0x38d138fd,0x2e173292,0x3990399d,0x3905395f,0x386b38a0,0xb024a471,0x3965397d,0x37e7388b,0x37e73831,0xb575b39f,0x39253947,0x34f63684,0x36da3764,0xb825b6f6,
0x39a439a8,0x399339a8,0x387638b4,0x2471306a,0x39853998,0x38ec3954,0x37cd3831,0xb319aea4,0x3947396a,0x3764385f,0x3684372d,0xb6f6b555,0x38ec391d,0x341235d1,0x351635d1,0xb8c7b831,
0x39a339a8,0x399039a8,0x380c385f,0xabc42c70,0x39783993,0x38d13947,0x36a13764,0xb4f6b209,0x39253954,0x36da3831,0x34f635d1,0xb825b6bd,0x38aa38ec,0x324d3516,0x324d3412,0xb941b8c7,
0x0,0x2c700000,0x0,0x385f3800,0x0,0x3292306a,0x0,0x38fd38b4,0x0,0x35553454,0x0,0x396a393a,0x0,0x372d3649,0x0,0x39a1398c,
0x20710000,0x2cfd0000,0x2cfd2c70,0x38be385f,0x26aa2471,0x335c30f5,0x2e172d8a,0x394d390e,0x298d2871,0x35ef34d6,0x2f302ea4,0x399b397d,0x2bc42aa9,0x37e736f6,0x30242fbd,0x39a339a8,
0x24710000,0x2d8a0000,0x30f5306a,0x390e38b4,0x2aa92871,0x3412317f,0x3209317f,0x39853954,0x2d8a2c70,0x36843555,0x33193292,0x39a839a1,0x2fbd2ea4,0x38493799,0x3412339f,0x39743998,
0x26aa0000,0x2e170000,0x335c3292,0x394d38fd,0x2cfd2aa9,0x34753209,0x34753412,0x39a33985,0x30242ea4,0x371235d1,0x353634d6,0x399039a6,0x31c430f5,0x38963819,0x35ef3594,0x3915395f,
0x28710000,0x2ea40000,0x34d63454,0x397d393a,0x2ea42c70,0x34d63292,0x35d13555,0x39a639a1,0x317f306a,0x37993649,0x36bd3649,0x3954398c,0x339f3292,0x38da385f,0x3799372d,0x388b38fd,
0x298d0000,0x2f300000,0x35ef3555,0x399b396a,0x30242d8a,0x35363319,0x37123684,0x399039a8,0x32d5317f,0x380c36bd,0x380c3799,0x38f53954,0x34b63412,0x391538a0,0x38803849,0x37b33876,
0x2aa90000,0x2fbd0000,0x36f63649,0x39a8398c,0x30f52ea4,0x3594339f,0x38193799,0x395f3998,0x34123292,0x3849372d,0x38a0385f,0x387638fd,0x359434d6,0x394738da,0x390e38da,0x360e3799,
0x2bc40000,0x30240000,0x37e7372d,0x39a339a1,0x31c42fbd,0x35ef3412,0x38963849,0x39153974,0x34b6339f,0x38803799,0x391538da,0x37b3388b,0x36673594,0x396f390e,0x396f3947,0x3433360e,
0x39a839a8,0xac700000,0x39a839a8,0xb85fb800,0x39a839a8,0xb292b06a,0x39a839a8,0xb8fdb8b4,0x39a839a8,0xb555b454,0x39a839a8,0xb96ab93a,0x39a839a8,0xb72db649,0x39a839a8,0xb9a1b98c,
0x3989398c,0xb2d5b06a,0x3965396a,0xb941b8fd,0x39813985,0xb5b2b496,0x3959395f,0xb996b974,0x3978397d,0xb7b3b6bd,0x394d3954,0xb9a5b9a6,0x396f3974,0xb8aab849,0x39413947,0xb96fb993,
0x392c393a,0xb594b454,0x38a038b4,0xb9a4b98c,0x390e391d,0xb7cdb6bd,0x3876388b,0xb993b9a6,0x38ec38fd,0xb8c7b85f,0x3849385f,0xb92cb96a,0x38c738da,0xb95fb91d,0x38193831,0xb876b8da,
0x389638b4,0xb77fb649,0x36da372d,0xb981b9a1,0x38543876,0xb8beb849,0x362b3684,0xb8f5b947,0x380c3831,0xb965b91d,0x357535d1,0xb80cb88b,0x377f37cd,0xb9a7b993,0x34b63516,0xb5b2b6f6,
0x37993800,0xb88bb800,0x339f3454,0xb8dab93a,0x36bd372d,0xb954b8fd,0x317f3292,0xb799b85f,0x35d13649,0xb9a6b98c,0x2ea4306a,0xb4d6b649,0x34d63555,0xb97db9a1,0x28712c70,0xaea4b292,
0x35b23649,0xb925b8b4,0x26aa2c70,0xb77fb85f,0x34753516,0xb99fb974,0xabc4a471,0xb475b60e,0x324d339f,0xb989b9a6,0xb0b0aea4,0xabc4b17f,0x2f3030f5,0xb8e3b947,0xb35cb209,0x313a2aa9,
0x33193454,0xb985b93a,0xb209b06a,0xb496b649,0x2fbd317f,0xb99db9a6,0xb496b39f,0xaaa9b17f,0x24712c70,0xb90eb96a,0xb60eb555,0x32092c70,0xad8aa871,0xb7cdb88b,0xb764b6bd,0x368434d6,
0x2cfd306a,0xb9a8b98c,0xb62bb555,0xacfdb292,0xa98d2471,0xb94db993,0xb7b3b6f6,0x31c42aa9,0xb13aaea4,0xb83db8da,0xb880b831,0x36a134d6,0xb475b319,0xb536b6f6,0xb905b8c7,0x38be3819,
0x0,0x39a139a8,0x0,0x372d3800,0x0,0x396a398c,0x0,0x35553649,0x0,0x38fd393a,0x0,0x32923454,0x0,0x385f38b4,0x0,0x2c70306a,
0x30b0306a,0x3965398c,0x32d53292,0x34333555,0x313a30f5,0x38e3392c,0x335c3319,0x2f303209,0x31c4317f,0x3825388b,0x33e2339f,0xa98d2871,0x324d3209,0x36673764,0x34333412,0xb24dafbd,
0x34963454,0x38ec393a,0x36843649,0x2aa9306a,0x351634d6,0x3819388b,0x36f636bd,0xafbda871,0x35943555,0x360e372d,0x3764372d,0xb496b292,0x360e35d1,0x331934d6,0x37cd3799,0xb6f6b5d1,
0x36a13649,0x383d38b4,0x3880385f,0xb13aac70,0x374936f6,0x362b3764,0x38be38a0,0xb575b412,0x37e73799,0x32d534d6,0x38f538da,0xb7e7b6bd,0x383d3819,0x26aa2fbd,0x3925390e,0xb8e3b876,
0x38313800,0x36bd3800,0x3954393a,0xb5d1b454,0x388b385f,0x339f3555,0x397d396a,0xb831b72d,0x38da38b4,0x2871306a,0x3998398c,0xb91db8b4,0x391d38fd,0xb17fac70,0x39a639a1,0xb998b96a,
0x38e338b4,0x34b63649,0x39a739a1,0xb83db72d,0x3933390e,0x2cfd3209,0x39a339a8,0xb933b8c7,0x396f3954,0xb0b0a871,0x39893998,0xb9a3b97d,0x39963985,0xb5b2b412,0x39593974,0xb981b9a4,
0x395f393a,0x30f53454,0x3974398c,0xb92cb8b4,0x3993397d,0xad8a2871,0x392c3954,0xb9a4b97d,0x39a839a1,0xb516b292,0x38c738fd,0xb974b9a1,0x399d39a6,0xb819b6bd,0x3849388b,0xb8a0b91d,
0x399f398c,0x2071306a,0x38be38fd,0xb99fb96a,0x39a539a8,0xb3e2afbd,0x38253876,0xb978b9a4,0x39813998,0xb77fb5d1,0x36da3799,0xb896b91d,0x3933395f,0xb905b876,0x3536360e,0xb62bb7cd,
0x34003400,0x34003400,0xb4003400,0xb4003400,0x34003400,0x34003400,0xb4003400,0xb4003400,0x34003400,0x34003400,0xb4003400,0xb4003400,0x34003400,0x34003400,0xb4003400,0xb4003400,
0x33643400,0xb364b400,0xb3643400,0x3364b400,0x2e1f31a8,0xae1fb1a8,0xae1f31a8,0x2e1fb1a8,0xae1f0000,0x2e1f0000,0x2e1f0000,0xae1f0000,0xb364b1a8,0x336431a8,0x3364b1a8,0xb36431a8,
0x31a83400,0x31a83400,0xb1a83400,0xb1a83400,0xb1a80000,0xb1a80000,0x31a80000,0x31a80000,0xb1a8b400,0xb1a8b400,0x31a8b400,0x31a8b400,0x31a80000,0x31a80000,0xb1a80000,0xb1a80000,
0x2e1f3400,0xae1fb400,0xae1f3400,0x2e1fb400,0xb364b1a8,0x336431a8,0x3364b1a8,0xb36431a8,0x33640000,0xb3640000,0xb3640000,0x33640000,0xae1f31a8,0x2e1fb1a8,0x2e1f31a8,0xae1fb1a8,
0x3400,0x3400,0x3400,0x3400,0xb400,0xb400,0xb400,0xb400,0x3400,0x3400,0x3400,0x3400,0xb400,0xb400,0xb400,0xb400,
0xae1f3400,0x2e1fb400,0x2e1f3400,0xae1fb400,0x3364b1a8,0xb36431a8,0xb364b1a8,0x336431a8,0xb3640000,0x33640000,0x33640000,0xb3640000,0x2e1f31a8,0xae1fb1a8,0xae1f31a8,0x2e1fb1a8,
0xb1a83400,0xb1a83400,0x31a83400,0x31a83400,0x31a80000,0x31a80000,0xb1a80000,0xb1a80000,0x31a8b400,0x31a8b400,0xb1a8b400,0xb1a8b400,0xb1a80000,0xb1a80000,0x31a80000,0x31a80000,
0xb3643400,0x3364b400,0x33643400,0xb364b400,0xae1f31a8,0x2e1fb1a8,0x2e1f31a8,0xae1fb1a8,0x2e1f0000,0xae1f0000,0xae1f0000,0x2e1f0000,0x3364b1a8,0xb36431a8,0xb364b1a8,0x336431a8,
0x0,0x0,0x0,0x0,0x0,0x0,0x0,0x0,0x0,0x0,0x0,0x0,0x0,0x0,0x0,0x0,
0x2e1f0000,0xae1f0000,0xae1f0000,0x2e1f0000,0x336431a8,0xb364b1a8,0xb36431a8,0x3364b1a8,0x33643400,0xb364b400,0xb3643400,0x3364b400,0x2e1f31a8,0xae1fb1a8,0xae1f31a8,0x2e1fb1a8,
0x31a80000,0x31a80000,0xb1a80000,0xb1a80000,0x31a83400,0x31a83400,0xb1a83400,0xb1a83400,0xb1a80000,0xb1a80000,0x31a80000,0x31a80000,0xb1a8b400,0xb1a8b400,0x31a8b400,0x31a8b400,
0x33640000,0xb3640000,0xb3640000,0x33640000,0xae1f31a8,0x2e1fb1a8,0x2e1f31a8,0xae1fb1a8,0xae1fb400,0x2e1f3400,0x2e1fb400,0xae1f3400,0x336431a8,0xb364b1a8,0xb36431a8,0x3364b1a8,
0x34000000,0x34000000,0xb4000000,0xb4000000,0xb4000000,0xb4000000,0x34000000,0x34000000,0x34000000,0x34000000,0xb4000000,0xb4000000,0xb4000000,0xb4000000,0x34000000,0x34000000,
0x33640000,0xb3640000,0xb3640000,0x33640000,0xae1fb1a8,0x2e1f31a8,0x2e1fb1a8,0xae1f31a8,0xae1f3400,0x2e1fb400,0x2e1f3400,0xae1fb400,0x3364b1a8,0xb36431a8,0xb364b1a8,0x336431a8,
0x31a80000,0x31a80000,0xb1a80000,0xb1a80000,0x31a8b400,0x31a8b400,0xb1a8b400,0xb1a8b400,0xb1a80000,0xb1a80000,0x31a80000,0x31a80000,0xb1a83400,0xb1a83400,0x31a83400,0x31a83400,
0x2e1f0000,0xae1f0000,0xae1f0000,0x2e1f0000,0x3364b1a8,0xb36431a8,0xb364b1a8,0x336431a8,0x3364b400,0xb3643400,0xb364b400,0x33643400,0x2e1fb1a8,0xae1f31a8,0xae1fb1a8,0x2e1f31a8,
0x0,0x0,0x0,0x0,0x0,0x0,0x0,0x0,0x0,0x0,0x0,0x0,0x0,0x0,0x0,0x0,
0xae1f0000,0x2e1f0000,0x2e1f0000,0xae1f0000,0xb364b1a8,0x336431a8,0x3364b1a8,0xb36431a8,0xb364b400,0x33643400,0x3364b400,0xb3643400,0xae1fb1a8,0x2e1f31a8,0x2e1fb1a8,0xae1f31a8,
0xb1a80000,0xb1a80000,0x31a80000,0x31a80000,0xb1a8b400,0xb1a8b400,0x31a8b400,0x31a8b400,0x31a80000,0x31a80000,0xb1a80000,0xb1a80000,0x31a83400,0x31a83400,0xb1a83400,0xb1a83400,
0xb3640000,0x33640000,0x33640000,0xb3640000,0x2e1fb1a8,0xae1f31a8,0xae1fb1a8,0x2e1f31a8,0x2e1f3400,0xae1fb400,0xae1f3400,0x2e1fb400,0xb364b1a8,0x336431a8,0x3364b1a8,0xb36431a8,
0xb4000000,0xb4000000,0x34000000,0x34000000,0x34000000,0x34000000,0xb4000000,0xb4000000,0xb4000000,0xb4000000,0x34000000,0x34000000,0x34000000,0x34000000,0xb4000000,0xb4000000,
0xb3640000,0x33640000,0x33640000,0xb3640000,0x2e1f31a8,0xae1fb1a8,0xae1f31a8,0x2e1fb1a8,0x2e1fb400,0xae1f3400,0xae1fb400,0x2e1f3400,0xb36431a8,0x3364b1a8,0x336431a8,0xb364b1a8,
0xb1a80000,0xb1a80000,0x31a80000,0x31a80000,0xb1a83400,0xb1a83400,0x31a83400,0x31a83400,0x31a80000,0x31a80000,0xb1a80000,0xb1a80000,0x31a8b400,0x31a8b400,0xb1a8b400,0xb1a8b400,
0xae1f0000,0x2e1f0000,0x2e1f0000,0xae1f0000,0xb36431a8,0x3364b1a8,0x336431a8,0xb364b1a8,0xb3643400,0x3364b400,0x33643400,0xb364b400,0xae1f31a8,0x2e1fb1a8,0x2e1f31a8,0xae1fb1a8,
0x33d93400,0xaa3e0000,0xb3d93400,0x2a3e0000,0x32a73364,0xb072ae1f,0xb2a73364,0x3072ae1f,0x307231a8,0xb2a7b1a8,0xb07231a8,0x32a7b1a8,0x2a3e2e1f,0xb3d9b364,0xaa3e2e1f,0x33d9b364,
0x32a73400,0x30720000,0xb2a73400,0xb0720000,0xaa3e2e1f,0x33d93364,0x2a3e2e1f,0xb3d93364,0xb3d9b1a8,0x2a3e31a8,0x33d9b1a8,0xaa3e31a8,0xb072b364,0xb2a7ae1f,0x3072b364,0x32a7ae1f,
0x30723400,0xb2a70000,0xb0723400,0x32a70000,0xb3d9ae1f,0xaa3eb364,0x33d9ae1f,0x2a3eb364,0x2a3eb1a8,0x33d931a8,0xaa3eb1a8,0xb3d931a8,0x32a73364,0xb0722e1f,0xb2a73364,0x30722e1f,
0x2a3e3400,0x33d90000,0xaa3e3400,0xb3d90000,0xb072b364,0xb2a72e1f,0x3072b364,0x32a72e1f,0x32a731a8,0x3072b1a8,0xb2a731a8,0xb072b1a8,0xb3d9ae1f,0xaa3e3364,0x33d9ae1f,0x2a3e3364,
0xaa3e3400,0xb3d90000,0x2a3e3400,0x33d90000,0x3072b364,0x32a72e1f,0xb072b364,0xb2a72e1f,0xb2a731a8,0xb072b1a8,0x32a731a8,0x3072b1a8,0x33d9ae1f,0x2a3e3364,0xb3d9ae1f,0xaa3e3364,
0xb0723400,0x32a70000,0x30723400,0xb2a70000,0x33d9ae1f,0x2a3eb364,0xb3d9ae1f,0xaa3eb364,0xaa3eb1a8,0xb3d931a8,0x2a3eb1a8,0x33d931a8,0xb2a73364,0x30722e1f,0x32a73364,0xb0722e1f,
0xb2a73400,0xb0720000,0x32a73400,0x30720000,0x2a3e2e1f,0xb3d93364,0xaa3e2e1f,0x33d93364,0x33d9b1a8,0xaa3e31a8,0xb3d9b1a8,0x2a3e31a8,0x3072b364,0x32a7ae1f,0xb072b364,0xb2a7ae1f,
0xb3d93400,0x2a3e0000,0x33d93400,0xaa3e0000,0xb2a73364,0x3072ae1f,0x32a73364,0xb072ae1f,0xb07231a8,0x32a7b1a8,0x307231a8,0xb2a7b1a8,0xaa3e2e1f,0x33d9b364,0x2a3e2e1f,0xb3d9b364,
0x2a3e0000,0x33d93400,0xaa3e0000,0xb3d93400,0x30722e1f,0x32a73364,0xb0722e1f,0xb2a73364,0x32a731a8,0x307231a8,0xb2a731a8,0xb07231a8,0x33d93364,0x2a3e2e1f,0xb3d93364,0xaa3e2e1f,
0x30720000,0xb2a7b400,0xb0720000,0x32a7b400,0x33d93364,0x2a3eae1f,0xb3d93364,0xaa3eae1f,0x2a3e31a8,0x33d931a8,0xaa3e31a8,0xb3d931a8,0xb2a7ae1f,0x30723364,0x32a7ae1f,0xb0723364,
0x32a70000,0x30723400,0xb2a70000,0xb0723400,0x2a3e3364,0xb3d9ae1f,0xaa3e3364,0x33d9ae1f,0xb3d9b1a8,0x2a3eb1a8,0x33d9b1a8,0xaa3eb1a8,0x3072ae1f,0x32a73364,0xb072ae1f,0xb2a73364,
0x33d90000,0xaa3eb400,0xb3d90000,0x2a3eb400,0xb2a72e1f,0x30723364,0x32a72e1f,0xb0723364,0x3072b1a8,0xb2a7b1a8,0xb072b1a8,0x32a7b1a8,0xaa3e3364,0x33d92e1f,0x2a3e3364,0xb3d92e1f,
0x33d90000,0xaa3e3400,0xb3d90000,0x2a3e3400,0xb2a7ae1f,0x3072b364,0x32a7ae1f,0xb072b364,0x307231a8,0xb2a731a8,0xb07231a8,0x32a731a8,0xaa3eb364,0x33d9ae1f,0x2a3eb364,0xb3d9ae1f,
0x32a70000,0x3072b400,0xb2a70000,0xb072b400,0x2a3eb364,0xb3d92e1f,0xaa3eb364,0x33d92e1f,0xb3d931a8,0x2a3e31a8,0x33d931a8,0xaa3e31a8,0x30722e1f,0x32a7b364,0xb0722e1f,0xb2a7b364,
0x30720000,0xb2a73400,0xb0720000,0x32a73400,0x33d9b364,0x2a3e2e1f,0xb3d9b364,0xaa3e2e1f,0x2a3eb1a8,0x33d9b1a8,0xaa3eb1a8,0xb3d9b1a8,0xb2a72e1f,0x3072b364,0x32a72e1f,0xb072b364,
0x2a3e0000,0x33d9b400,0xaa3e0000,0xb3d9b400,0x3072ae1f,0x32a7b364,0xb072ae1f,0xb2a7b364,0x32a7b1a8,0x3072b1a8,0xb2a7b1a8,0xb072b1a8,0x33d9b364,0x2a3eae1f,0xb3d9b364,0xaa3eae1f,
0xaa3e0000,0xb3d9b400,0x2a3e0000,0x33d9b400,0xb072ae1f,0xb2a7b364,0x3072ae1f,0x32a7b364,0xb2a7b1a8,0xb072b1a8,0x32a7b1a8,0x3072b1a8,0xb3d9b364,0xaa3eae1f,0x33d9b364,0x2a3eae1f,
0xb0720000,0x32a73400,0x30720000,0xb2a73400,0xb3d9b364,0xaa3e2e1f,0x33d9b364,0x2a3e2e1f,0xaa3eb1a8,0xb3d9b1a8,0x2a3eb1a8,0x33d9b1a8,0x32a72e1f,0xb072b364,0xb2a72e1f,0x3072b364,
0xb2a70000,0xb072b400,0x32a70000,0x3072b400,0xaa3eb364,0x33d92e1f,0x2a3eb364,0xb3d92e1f,0x33d931a8,0xaa3e31a8,0xb3d931a8,0x2a3e31a8,0xb0722e1f,0xb2a7b364,0x30722e1f,0x32a7b364,
0xb3d90000,0x2a3e3400,0x33d90000,0xaa3e3400,0x32a7ae1f,0xb072b364,0xb2a7ae1f,0x3072b364,0xb07231a8,0x32a731a8,0x307231a8,0xb2a731a8,0x2a3eb364,0xb3d9ae1f,0xaa3eb364,0x33d9ae1f,
0xb3d90000,0x2a3eb400,0x33d90000,0xaa3eb400,0x32a72e1f,0xb0723364,0xb2a72e1f,0x30723364,0xb072b1a8,0x32a7b1a8,0x3072b1a8,0xb2a7b1a8,0x2a3e3364,0xb3d92e1f,0xaa3e3364,0x33d92e1f,
0xb2a70000,0xb0723400,0x32a70000,0x30723400,0xaa3e3364,0x33d9ae1f,0x2a3e3364,0xb3d9ae1f,0x33d9b1a8,0xaa3eb1a8,0xb3d9b1a8,0x2a3eb1a8,0xb072ae1f,0xb2a73364,0x3072ae1f,0x32a73364,
0xb0720000,0x32a7b400,0x30720000,0xb2a7b400,0xb3d93364,0xaa3eae1f,0x33d93364,0x2a3eae1f,0xaa3e31a8,0xb3d931a8,0x2a3e31a8,0x33d931a8,0x32a7ae1f,0xb0723364,0xb2a7ae1f,0x30723364,
0xaa3e0000,0xb3d93400,0x2a3e0000,0x33d93400,0xb0722e1f,0xb2a73364,0x30722e1f,0x32a73364,0xb2a731a8,0xb07231a8,0x32a731a8,0x307231a8,0xb3d93364,0xaa3e2e1f,0x33d93364,0x2a3e2e1f,
0x3c003c00,0x3c00,0xbc003c00,0x3c00,0x3c003c00,0x0,0xbc003c00,0x0,0x3c003c00,0x0,0xbc003c00,0x0,0x3c003c00,0x0,0xbc003c00,0x0,
0x3b643c00,0xb61fbc00,0xbb643c00,0x361fbc00,0x361f39a8,0xbb64b9a8,0xb61f39a8,0x3b64b9a8,0xb61f0000,0xbb64bc00,0x361f0000,0x3b64bc00,0xbb64b9a8,0xb61fb9a8,0x3b64b9a8,0x361fb9a8,
0x39a83c00,0xb9a83c00,0xb9a83c00,0x39a83c00,0xb9a80000,0xb9a8bc00,0x39a80000,0x39a8bc00,0xb9a8bc00,0x39a80000,0x39a8bc00,0xb9a80000,0x39a80000,0x39a83c00,0xb9a80000,0xb9a83c00,
0x361f3c00,0xbb64bc00,0xb61f3c00,0x3b64bc00,0xbb64b9a8,0x361fb9a8,0x3b64b9a8,0xb61fb9a8,0x3b640000,0x361f3c00,0xbb640000,0xb61f3c00,0xb61f39a8,0xbb64b9a8,0x361f39a8,0x3b64b9a8,
0x3c00,0xbc003c00,0x3c00,0x3c003c00,0xbc00,0x3c000000,0xbc00,0xbc000000,0x3c00,0xbc000000,0x3c00,0x3c000000,0xbc00,0x3c000000,0xbc00,0xbc000000,
0xb61f3c00,0xbb64bc00,0x361f3c00,0x3b64bc00,0x3b64b9a8,0x361f39a8,0xbb64b9a8,0xb61f39a8,0xbb640000,0x361fbc00,0x3b640000,0xb61fbc00,0x361f39a8,0xbb6439a8,0xb61f39a8,0x3b6439a8,
0xb9a83c00,0xb9a83c00,0x39a83c00,0x39a83c00,0x39a80000,0xb9a83c00,0xb9a80000,0x39a83c00,0x39a8bc00,0x39a80000,0xb9a8bc00,0xb9a80000,0xb9a80000,0x39a8bc00,0x39a80000,0xb9a8bc00,
0xbb643c00,0xb61fbc00,0x3b643c00,0x361fbc00,0xb61f39a8,0xbb6439a8,0x361f39a8,0x3b6439a8,0x361f0000,0xbb643c00,0xb61f0000,0x3b643c00,0x3b64b9a8,0xb61f39a8,0xbb64b9a8,0x361f39a8,
0x3400,0x3400,0x3400,0x3400,0x3400,0xb400,0x3400,0xb400,0x3400,0x3400,0x3400,0x3400,0x3400,0xb400,0x3400,0xb400,
0x3400,0x3400,0x34000000,0x34000000,0x2e1f3364,0xae1fb364,0x3364ae1f,0xb3642e1f,0x31a831a8,0x31a831a8,0x31a8b1a8,0x31a8b1a8,0x33642e1f,0xb364ae1f,0x2e1fb364,0xae1f3364,
0x3400,0x3400,0xb400,0xb400,0x31a831a8,0xb1a8b1a8,0xb1a8b1a8,0x31a831a8,0x34000000,0x34000000,0xb4000000,0xb4000000,0x31a8b1a8,0xb1a831a8,0xb1a831a8,0x31a8b1a8,
0x3400,0x3400,0xb4000000,0xb4000000,0x33642e1f,0xb364ae1f,0xae1f3364,0x2e1fb364,0x31a8b1a8,0x31a8b1a8,0x31a831a8,0x31a831a8,0xae1fb364,0x2e1f3364,0x3364ae1f,0xb3642e1f,
0x3400,0x3400,0x3400,0x3400,0x34000000,0xb4000000,0x34000000,0xb4000000,0xb400,0xb400,0xb400,0xb400,0xb4000000,0x34000000,0xb4000000,0x34000000,
0x3400,0x3400,0x34000000,0x34000000,0x3364ae1f,0xb3642e1f,0xae1fb364,0x2e1f3364,0xb1a8b1a8,0xb1a8b1a8,0xb1a831a8,0xb1a831a8,0xae1f3364,0x2e1fb364,0x33642e1f,0xb364ae1f,
0x3400,0x3400,0xb400,0xb400,0x31a8b1a8,0xb1a831a8,0xb1a831a8,0x31a8b1a8,0xb4000000,0xb4000000,0x34000000,0x34000000,0x31a831a8,0xb1a8b1a8,0xb1a8b1a8,0x31a831a8,
0x3400,0x3400,0xb4000000,0xb4000000,0x2e1fb364,0xae1f3364,0x33642e1f,0xb364ae1f,0xb1a831a8,0xb1a831a8,0xb1a8b1a8,0xb1a8b1a8,0x3364ae1f,0xb3642e1f,0x2e1f3364,0xae1fb364,
0x3400,0x3400,0x3400,0x3400,0x3400,0xb400,0x3400,0xb400,0x3400,0x3400,0x3400,0x3400,0x3400,0xb400,0x3400,0xb400,
0xb400,0xb400,0xb4000000,0xb4000000,0xae1fb364,0x2e1f3364,0xb3642e1f,0x3364ae1f,0xb1a8b1a8,0xb1a8b1a8,0xb1a831a8,0xb1a831a8,0xb364ae1f,0x33642e1f,0xae1f3364,0x2e1fb364,
0x3400,0x3400,0xb400,0xb400,0x31a831a8,0xb1a8b1a8,0xb1a8b1a8,0x31a831a8,0x34000000,0x34000000,0xb4000000,0xb4000000,0x31a8b1a8,0xb1a831a8,0xb1a831a8,0x31a8b1a8,
0xb400,0xb400,0x34000000,0x34000000,0xb364ae1f,0x33642e1f,0x2e1fb364,0xae1f3364,0xb1a831a8,0xb1a831a8,0xb1a8b1a8,0xb1a8b1a8,0x2e1f3364,0xae1fb364,0xb3642e1f,0x3364ae1f,
0x3400,0x3400,0x3400,0x3400,0x34000000,0xb4000000,0x34000000,0xb4000000,0xb400,0xb400,0xb400,0xb400,0xb4000000,0x34000000,0xb4000000,0x34000000,
0xb400,0xb400,0xb4000000,0xb4000000,0xb3642e1f,0x3364ae1f,0x2e1f3364,0xae1fb364,0x31a831a8,0x31a831a8,0x31a8b1a8,0x31a8b1a8,0x2e1fb364,0xae1f3364,0xb364ae1f,0x33642e1f,
0x3400,0x3400,0xb400,0xb400,0x31a8b1a8,0xb1a831a8,0xb1a831a8,0x31a8b1a8,0xb4000000,0xb4000000,0x34000000,0x34000000,0x31a831a8,0xb1a8b1a8,0xb1a8b1a8,0x31a831a8,
0xb400,0xb400,0x34000000,0x34000000,0xae1f3364,0x2e1fb364,0xb364ae1f,0x33642e1f,0x31a8b1a8,0x31a8b1a8,0x31a831a8,0x31a831a8,0xb3642e1f,0x3364ae1f,0xae1fb364,0x2e1f3364,
0x34000000,0x34000000,0x34000000,0x34000000,0x34000000,0xb4000000,0x34000000,0xb4000000,0x34000000,0x34000000,0x34000000,0x34000000,0x34000000,0xb4000000,0x34000000,0xb4000000,
0x34000000,0x34000000,0xb400,0xb400,0x3364ae1f,0xb3642e1f,0xae1fb364,0x2e1f3364,0x31a8b1a8,0x31a8b1a8,0xb1a8b1a8,0xb1a8b1a8,0x2e1fb364,0xae1f3364,0xb364ae1f,0x33642e1f,
0x34000000,0x34000000,0xb4000000,0xb4000000,0x31a8b1a8,0xb1a831a8,0xb1a831a8,0x31a8b1a8,0xb400,0xb400,0x3400,0x3400,0xb1a8b1a8,0x31a831a8,0x31a831a8,0xb1a8b1a8,
0x34000000,0x34000000,0x3400,0x3400,0x2e1fb364,0xae1f3364,0x33642e1f,0xb364ae1f,0xb1a8b1a8,0xb1a8b1a8,0x31a8b1a8,0x31a8b1a8,0xb3642e1f,0x3364ae1f,0xae1fb364,0x2e1f3364,
0x34000000,0x34000000,0x34000000,0x34000000,0xb400,0x3400,0xb400,0x3400,0xb4000000,0xb4000000,0xb4000000,0xb4000000,0x3400,0xb400,0x3400,0xb400,
0x34000000,0x34000000,0xb400,0xb400,0xae1fb364,0x2e1f3364,0xb3642e1f,0x3364ae1f,0xb1a831a8,0xb1a831a8,0x31a831a8,0x31a831a8,0x33642e1f,0xb364ae1f,0x2e1fb364,0xae1f3364,
0x34000000,0x34000000,0xb4000000,0xb4000000,0xb1a8b1a8,0x31a831a8,0x31a831a8,0xb1a8b1a8,0x3400,0x3400,0xb400,0xb400,0x31a8b1a8,0xb1a831a8,0xb1a831a8,0x31a8b1a8,
0x34000000,0x34000000,0x3400,0x3400,0xb364ae1f,0x33642e1f,0x2e1fb364,0xae1f3364,0x31a831a8,0x31a831a8,0xb1a831a8,0xb1a831a8,0xae1fb364,0x2e1f3364,0x3364ae1f,0xb3642e1f,
0x34000000,0x34000000,0x34000000,0x34000000,0x34000000,0xb4000000,0x34000000,0xb4000000,0x34000000,0x34000000,0x34000000,0x34000000,0x34000000,0xb4000000,0x34000000,0xb4000000,
0xb4000000,0xb4000000,0x3400,0x3400,0xb3642e1f,0x3364ae1f,0x2e1f3364,0xae1fb364,0xb1a831a8,0xb1a831a8,0x31a831a8,0x31a831a8,0xae1f3364,0x2e1fb364,0x33642e1f,0xb364ae1f,
0x34000000,0x34000000,0xb4000000,0xb4000000,0x31a8b1a8,0xb1a831a8,0xb1a831a8,0x31a8b1a8,0xb400,0xb400,0x3400,0x3400,0xb1a8b1a8,0x31a831a8,0x31a831a8,0xb1a8b1a8,
0xb4000000,0xb4000000,0xb400,0xb400,0xae1f3364,0x2e1fb364,0xb364ae1f,0x33642e1f,0x31a831a8,0x31a831a8,0xb1a831a8,0xb1a831a8,0x3364ae1f,0xb3642e1f,0x2e1f3364,0xae1fb364,
0x34000000,0x34000000,0x34000000,0x34000000,0xb400,0x3400,0xb400,0x3400,0xb4000000,0xb4000000,0xb4000000,0xb4000000,0x3400,0xb400,0x3400,0xb400,
0xb4000000,0xb4000000,0x3400,0x3400,0x2e1f3364,0xae1fb364,0x3364ae1f,0xb3642e1f,0x31a8b1a8,0x31a8b1a8,0xb1a8b1a8,0xb1a8b1a8,0xb364ae1f,0x33642e1f,0xae1f3364,0x2e1fb364,
0x34000000,0x34000000,0xb4000000,0xb4000000,0xb1a8b1a8,0x31a831a8,0x31a831a8,0xb1a8b1a8,0x3400,0x3400,0xb400,0xb400,0x31a8b1a8,0xb1a831a8,0xb1a831a8,0x31a8b1a8,
0xb4000000,0xb4000000,0xb400,0xb400,0x33642e1f,0xb364ae1f,0xae1f3364,0x2e1fb364,0xb1a8b1a8,0xb1a8b1a8,0x31a8b1a8,0x31a8b1a8,0x2e1f3364,0xae1fb364,0xb3642e1f,0x3364ae1f,
0x35a835a8,0x353a35a8,0x0,0x30540000,0x35a835a8,0x30543400,0x0,0x353a3400,0x35a835a8,0xb0540000,0x0,0x353a35a8,0x35a835a8,0xb53ab400,0x0,0x30543400,
0x35a635a8,0x351d35a8,0x24710000,0x30d60000,0x359835a1,0x2d7f332d,0x2aa42870,0x357d345f,0x357d358c,0xb2bdac6a,0x2d7f2c6a,0x348b358c,0x3554356a,0xb5a6b4fd,0x2f9f2e92,0x24713155,
0x35a135a8,0x34fd35a8,0x28700000,0x31550000,0x356a358c,0x28703249,0x2e922c6a,0x35a134b4,0x34fd353a,0xb45fb054,0x31553054,0x332d353a,0x345f34b4,0xb56ab58c,0x332d3249,0xae922c6a,
0x359835a8,0x34da35a8,0x2aa40000,0x31d10000,0x351d356a,0xa4713155,0x30d62e92,0x35a634fd,0x343134b4,0xb51db249,0x33993249,0x30d634b4,0x31d1332d,0xb48bb5a1,0x34da345f,0xb2bda870,
0x358c35a8,0x34b435a8,0x2c6a0000,0x32490000,0x34b4353a,0xac6a3054,0x32493054,0x358c353a,0x32493400,0xb58cb400,0x34b43400,0x2c6a3400,0x2c6a3054,0xb249b53a,0x358c353a,0xb4b4b054,
0x357d35a8,0x348b35a8,0x2d7f0000,0x32bd0000,0x343134fd,0xaf9f2e92,0x33993155,0x3554356a,0x2f9f3249,0xb5a6b4b4,0x355434b4,0xa4713249,0xaaa42870,0xad7fb45f,0x359835a1,0xb57db32d,
0x356a35a8,0x345f35a8,0x2e920000,0x332d0000,0x332d34b4,0xb1552c6a,0x345f3249,0x34fd358c,0x28703054,0xb56ab53a,0x35a1353a,0xae923054,0xb155ac6a,0x2870b249,0x34fd358c,0xb5a1b4b4,
0x355435a8,0x343135a8,0x2f9f0000,0x33990000,0x31d1345f,0xb2bd2870,0x34da332d,0x348b35a1,0xaaa42c6a,0xb4dab58c,0x3598358c,0xb1d12c6a,0xb431b155,0x30d6ae92,0x339934fd,0xb51db56a,
0x3c003c00,0x0,0x0,0x3c003c00,0x3c003c00,0x0,0x0,0x3c003c00,0x3c003c00,0x0,0x0,0x3c003c00,0x3c003c00,0x0,0x0,0x3c003c00,
0x39a83c00,0x39a80000,0xb9a80000,0x39a83c00,0xb9a80000,0x39a83c00,0xb9a8bc00,0xb9a80000,0xb9a8bc00,0xb9a80000,0x39a80000,0xb9a8bc00,0x39a80000,0xb9a8bc00,0x39a83c00,0x39a80000,
0x3c00,0x3c000000,0xbc000000,0x3c00,0xbc00,0xbc000000,0x3c000000,0xbc00,0x3c00,0x3c000000,0xbc000000,0x3c00,0xbc00,0xbc000000,0x3c000000,0xbc00,
0xb9a83c00,0x39a80000,0xb9a80000,0xb9a83c00,0x39a80000,0x39a8bc00,0xb9a83c00,0x39a80000,0x39a8bc00,0xb9a80000,0x39a80000,0x39a8bc00,0xb9a80000,0xb9a83c00,0x39a8bc00,0xb9a80000,
0xbc003c00,0x0,0x0,0xbc003c00,0xbc003c00,0x0,0x0,0xbc003c00,0xbc003c00,0x0,0x0,0xbc003c00,0xbc003c00,0x0,0x0,0xbc003c00,
0xb9a83c00,0xb9a80000,0x39a80000,0xb9a83c00,0x39a80000,0xb9a83c00,0x39a8bc00,0x39a80000,0x39a8bc00,0x39a80000,0xb9a80000,0x39a8bc00,0xb9a80000,0x39a8bc00,0xb9a83c00,0xb9a80000,
0x3c00,0xbc000000,0x3c000000,0x3c00,0xbc00,0x3c000000,0xbc000000,0xbc00,0x3c00,0xbc000000,0x3c000000,0x3c00,0xbc00,0x3c000000,0xbc000000,0xbc00,
0x39a83c00,0xb9a80000,0x39a80000,0x39a83c00,0xb9a80000,0xb9a8bc00,0x39a83c00,0xb9a80000,0xb9a8bc00,0x39a80000,0xb9a80000,0xb9a8bc00,0x39a80000,0x39a83c00,0xb9a8bc00,0x39a80000,
0x3c003c00,0x0,0x0,0x3c003c00,0x3c003c00,0x0,0x0,0x3c003c00,0x3c003c00,0x0,0x0,0x3c003c00,0x3c003c00,0x0,0x0,0x3c003c00,
0x39a83c00,0x39a80000,0xb9a80000,0x39a83c00,0xb9a80000,0x39a83c00,0xb9a8bc00,0xb9a80000,0xb9a8bc00,0xb9a80000,0x39a80000,0xb9a8bc00,0x39a80000,0xb9a8bc00,0x39a83c00,0x39a80000,
0x3c00,0x3c000000,0xbc000000,0x3c00,0xbc00,0xbc000000,0x3c000000,0xbc00,0x3c00,0x3c000000,0xbc000000,0x3c00,0xbc00,0xbc000000,0x3c000000,0xbc00,
0xb9a83c00,0x39a80000,0xb9a80000,0xb9a83c00,0x39a80000,0x39a8bc00,0xb9a83c00,0x39a80000,0x39a8bc00,0xb9a80000,0x39a80000,0x39a8bc00,0xb9a80000,0xb9a83c00,0x39a8bc00,0xb9a80000,
0xbc003c00,0x0,0x0,0xbc003c00,0xbc003c00,0x0,0x0,0xbc003c00,0xbc003c00,0x0,0x0,0xbc003c00,0xbc003c00,0x0,0x0,0xbc003c00,
0xb9a83c00,0xb9a80000,0x39a80000,0xb9a83c00,0x39a80000,0xb9a83c00,0x39a8bc00,0x39a80000,0x39a8bc00,0x39a80000,0xb9a80000,0x39a8bc00,0xb9a80000,0x39a8bc00,0xb9a83c00,0xb9a80000,
0x3c00,0xbc000000,0x3c000000,0x3c00,0xbc00,0x3c000000,0xbc000000,0xbc00,0x3c00,0xbc000000,0x3c000000,0x3c00,0xbc00,0x3c000000,0xbc000000,0xbc00,
0x39a83c00,0xb9a80000,0x39a80000,0x39a83c00,0xb9a80000,0xb9a8bc00,0x39a83c00,0xb9a80000,0xb9a8bc00,0x39a80000,0xb9a80000,0xb9a8bc00,0x39a80000,0x39a83c00,0xb9a8bc00,0x39a80000,
0x2da82da8,0x2da82da8,0x0,0x0,0x2da82da8,0x2da82da8,0x0,0x0,0x2da82da8,0x2da82da8,0x0,0x0,0x2da82da8,0x2da82da8,0x0,0x0,
0x2da62da8,0x2d1d2d3a,0x1c710000,0x28d62854,0x2d982da1,0x2cda2cfd,0x22a42070,0x29d12955,0x2d7d2d8c,0x2c8b2cb4,0x257f246a,0x2abd2a49,0x2d542d6a,0x2c312c5f,0x279f2692,0x2b992b2d,
0x2da12da8,0x2b2d2c00,0x20700000,0x2c5f2c00,0x2d6a2d8c,0x29552a49,0x2692246a,0x2cfd2cb4,0x2cfd2d3a,0x26922854,0x29552854,0x2d6a2d3a,0x2c5f2cb4,0x2070246a,0x2b2d2a49,0x2da12d8c,
0x2d982da8,0x257f2854,0x22a40000,0x2d7d2d3a,0x2d1d2d6a,0x9c712070,0x28d62692,0x2da62da1,0x2c312cb4,0xa79fa46a,0x2b992a49,0x2d542d8c,0x29d12b2d,0xaabda955,0x2cda2c5f,0x2c8b2cfd,
0x2d8c2da8,0xa46a0000,0x246a0000,0x2d8c2da8,0x2cb42d3a,0xaa49a854,0x2a492854,0x2cb42d3a,0x2a492c00,0xacb4ac00,0x2cb42c00,0x2a492c00,0x246a2854,0xad8cad3a,0x2d8c2d3a,0x246a2854,
0x2d7d2da8,0xaabda854,0x257f0000,0x2c8b2d3a,0x2c312cfd,0xad1dac5f,0x2b992955,0x28d62b2d,0x279f2a49,0xada6ad8c,0x2d542cb4,0x9c71246a,0xa2a42070,0xacdaad6a,0x2d982da1,0xa9d1a692,
0x2d6a2da8,0xacfdac00,0x26920000,0x29552c00,0x2b2d2cb4,0xada1ad8c,0x2c5f2a49,0xa070246a,0x20702854,0xac5fad3a,0x2da12d3a,0xab2da854,0xa955a46a,0xa692aa49,0x2cfd2d8c,0xad6aacb4,
0x2d542da8,0xada6ad3a,0x279f0000,0x1c712854,0x29d12c5f,0xac8bad6a,0x2cda2b2d,0xaabda692,0xa2a4246a,0xa57faa49,0x2d982d8c,0xad7dacb4,0xac31a955,0x28d62070,0x2b992cfd,0xad1dada1,
0x34003400,0x34003400,0x0,0x0,0x34003400,0x34003400,0x0,0x0,0x34003400,0x34003400,0x0,0x0,0x34003400,0x34003400,0x0,0x0,
0x0,0x0,0x34003400,0x34003400,0x0,0x0,0x34003400,0x34003400,0x0,0x0,0x34003400,0x34003400,0x0,0x0,0x34003400,0x34003400,
0x33643400,0xb364b400,0xae1f0000,0x2e1f0000,0x2e1f31a8,0xae1fb1a8,0xb364b1a8,0x336431a8,0xae1f0000,0x2e1f0000,0xb364b400,0x33643400,0xb364b1a8,0x336431a8,0xae1fb1a8,0x2e1f31a8,
0x2e1f0000,0xae1f0000,0x33643400,0xb364b400,0x336431a8,0xb364b1a8,0x2e1f31a8,0xae1fb1a8,0x33643400,0xb364b400,0xae1f0000,0x2e1f0000,0x2e1f31a8,0xae1fb1a8,0xb364b1a8,0x336431a8,
0x31a83400,0x31a83400,0xb1a80000,0xb1a80000,0xb1a80000,0xb1a80000,0xb1a8b400,0xb1a8b400,0xb1a8b400,0xb1a8b400,0x31a80000,0x31a80000,0x31a80000,0x31a80000,0x31a83400,0x31a83400,
0x31a80000,0x31a80000,0x31a83400,0x31a83400,0x31a83400,0x31a83400,0xb1a80000,0xb1a80000,0xb1a80000,0xb1a80000,0xb1a8b400,0xb1a8b400,0xb1a8b400,0xb1a8b400,0x31a80000,0x31a80000,
0x2e1f3400,0xae1fb400,0xb3640000,0x33640000,0xb364b1a8,0x336431a8,0x2e1fb1a8,0xae1f31a8,0x33640000,0xb3640000,0x2e1f3400,0xae1fb400,0xae1f31a8,0x2e1fb1a8,0xb364b1a8,0x336431a8,
0x33640000,0xb3640000,0x2e1f3400,0xae1fb400,0xae1f31a8,0x2e1fb1a8,0xb364b1a8,0x336431a8,0xae1fb400,0x2e1f3400,0x33640000,0xb3640000,0x336431a8,0xb364b1a8,0xae1f31a8,0x2e1fb1a8,
0x3400,0x3400,0xb4000000,0xb4000000,0xb400,0xb400,0x34000000,0x34000000,0x3400,0x3400,0xb4000000,0xb4000000,0xb400,0xb400,0x34000000,0x34000000,
0x34000000,0x34000000,0x3400,0x3400,0xb4000000,0xb4000000,0xb400,0xb400,0x34000000,0x34000000,0x3400,0x3400,0xb4000000,0xb4000000,0xb400,0xb400,
0xae1f3400,0x2e1fb400,0xb3640000,0x33640000,0x3364b1a8,0xb36431a8,0x2e1f31a8,0xae1fb1a8,0xb3640000,0x33640000,0x2e1fb400,0xae1f3400,0x2e1f31a8,0xae1fb1a8,0xb36431a8,0x3364b1a8,
0x33640000,0xb3640000,0xae1f3400,0x2e1fb400,0xae1fb1a8,0x2e1f31a8,0x3364b1a8,0xb36431a8,0xae1f3400,0x2e1fb400,0xb3640000,0x33640000,0x3364b1a8,0xb36431a8,0x2e1f31a8,0xae1fb1a8,
0xb1a83400,0xb1a83400,0xb1a80000,0xb1a80000,0x31a80000,0x31a80000,0xb1a83400,0xb1a83400,0x31a8b400,0x31a8b400,0x31a80000,0x31a80000,0xb1a80000,0xb1a80000,0x31a8b400,0x31a8b400,
0x31a80000,0x31a80000,0xb1a83400,0xb1a83400,0x31a8b400,0x31a8b400,0x31a80000,0x31a80000,0xb1a80000,0xb1a80000,0x31a8b400,0x31a8b400,0xb1a83400,0xb1a83400,0xb1a80000,0xb1a80000,
0xb3643400,0x3364b400,0xae1f0000,0x2e1f0000,0xae1f31a8,0x2e1fb1a8,0xb36431a8,0x3364b1a8,0x2e1f0000,0xae1f0000,0xb3643400,0x3364b400,0x3364b1a8,0xb36431a8,0xae1f31a8,0x2e1fb1a8,
0x2e1f0000,0xae1f0000,0xb3643400,0x3364b400,0x3364b1a8,0xb36431a8,0xae1f31a8,0x2e1fb1a8,0x3364b400,0xb3643400,0x2e1f0000,0xae1f0000,0x2e1fb1a8,0xae1f31a8,0x3364b1a8,0xb36431a8,
0xb4003400,0xb4003400,0x0,0x0,0xb4003400,0xb4003400,0x0,0x0,0xb4003400,0xb4003400,0x0,0x0,0xb4003400,0xb4003400,0x0,0x0,
0x0,0x0,0xb4003400,0xb4003400,0x0,0x0,0xb4003400,0xb4003400,0x0,0x0,0xb4003400,0xb4003400,0x0,0x0,0xb4003400,0xb4003400,
0xb3643400,0x3364b400,0x2e1f0000,0xae1f0000,0xae1f31a8,0x2e1fb1a8,0x3364b1a8,0xb36431a8,0x2e1f0000,0xae1f0000,0x3364b400,0xb3643400,0x3364b1a8,0xb36431a8,0x2e1fb1a8,0xae1f31a8,
0xae1f0000,0x2e1f0000,0xb3643400,0x3364b400,0xb36431a8,0x3364b1a8,0xae1f31a8,0x2e1fb1a8,0xb3643400,0x3364b400,0x2e1f0000,0xae1f0000,0xae1f31a8,0x2e1fb1a8,0x3364b1a8,0xb36431a8,
0xb1a83400,0xb1a83400,0x31a80000,0x31a80000,0x31a80000,0x31a80000,0x31a8b400,0x31a8b400,0x31a8b400,0x31a8b400,0xb1a80000,0xb1a80000,0xb1a80000,0xb1a80000,0xb1a83400,0xb1a83400,
0xb1a80000,0xb1a80000,0xb1a83400,0xb1a83400,0xb1a83400,0xb1a83400,0x31a80000,0x31a80000,0x31a80000,0x31a80000,0x31a8b400,0x31a8b400,0x31a8b400,0x31a8b400,0xb1a80000,0xb1a80000,
0xae1f3400,0x2e1fb400,0x33640000,0xb3640000,0x3364b1a8,0xb36431a8,0xae1fb1a8,0x2e1f31a8,0xb3640000,0x33640000,0xae1f3400,0x2e1fb400,0x2e1f31a8,0xae1fb1a8,0x3364b1a8,0xb36431a8,
0xb3640000,0x33640000,0xae1f3400,0x2e1fb400,0x2e1f31a8,0xae1fb1a8,0x3364b1a8,0xb36431a8,0x2e1fb400,0xae1f3400,0xb3640000,0x33640000,0xb36431a8,0x3364b1a8,0x2e1f31a8,0xae1fb1a8,
0x3400,0x3400,0x34000000,0x34000000,0xb400,0xb400,0xb4000000,0xb4000000,0x3400,0x3400,0x34000000,0x34000000,0xb400,0xb400,0xb4000000,0xb4000000,
0xb4000000,0xb4000000,0x3400,0x3400,0x34000000,0x34000000,0xb400,0xb400,0xb4000000,0xb4000000,0x3400,0x3400,0x34000000,0x34000000,0xb400,0xb400,
0x2e1f3400,0xae1fb400,0x33640000,0xb3640000,0xb364b1a8,0x336431a8,0xae1f31a8,0x2e1fb1a8,0x33640000,0xb3640000,0xae1fb400,0x2e1f3400,0xae1f31a8,0x2e1fb1a8,0x336431a8,0xb364b1a8,
0xb3640000,0x33640000,0x2e1f3400,0xae1fb400,0x2e1fb1a8,0xae1f31a8,0xb364b1a8,0x336431a8,0x2e1f3400,0xae1fb400,0x33640000,0xb3640000,0xb364b1a8,0x336431a8,0xae1f31a8,0x2e1fb1a8,
0x31a83400,0x31a83400,0x31a80000,0x31a80000,0xb1a80000,0xb1a80000,0x31a83400,0x31a83400,0xb1a8b400,0xb1a8b400,0xb1a80000,0xb1a80000,0x31a80000,0x31a80000,0xb1a8b400,0xb1a8b400,
0xb1a80000,0xb1a80000,0x31a83400,0x31a83400,0xb1a8b400,0xb1a8b400,0xb1a80000,0xb1a80000,0x31a80000,0x31a80000,0xb1a8b400,0xb1a8b400,0x31a83400,0x31a83400,0x31a80000,0x31a80000,
0x33643400,0xb364b400,0x2e1f0000,0xae1f0000,0x2e1f31a8,0xae1fb1a8,0x336431a8,0xb364b1a8,0xae1f0000,0x2e1f0000,0x33643400,0xb364b400,0xb364b1a8,0x336431a8,0x2e1f31a8,0xae1fb1a8,
0xae1f0000,0x2e1f0000,0x33643400,0xb364b400,0xb364b1a8,0x336431a8,0x2e1f31a8,0xae1fb1a8,0xb364b400,0x33643400,0xae1f0000,0x2e1f0000,0xae1fb1a8,0x2e1f31a8,0xb364b1a8,0x336431a8,
0x3400,0x3400,0x264633f6,0x264633f6,0x1e4833ff,0x9e48b3ff,0x27d633f1,0xa7d6b3f1,0x224833fe,0x224833fe,0x28b233ea,0x28b233ea,0x24b533fa,0xa4b5b3fa,0x297933e2,0xa979b3e2,
0x3400,0x3400,0x33f6a646,0x33f6a646,0x2e7c3350,0xae7cb350,0x32f6afe3,0xb2f62fe3,0x31ed315f,0x31ed315f,0x30c4b26d,0x30c4b26d,0x33992d05,0xb399ad05,0x2b03b3ce,0xab0333ce,
0x3400,0x3400,0xa646b3f6,0xa646b3f6,0x31cb3184,0xb1cbb184,0xb24fb0ec,0x324f30ec,0x33fea248,0x33fea248,0xb3ea28b2,0xb3ea28b2,0x313ab20f,0xb13a320f,0xb09b328a,0x309bb28a,
0x3400,0x3400,0xb3f62646,0xb3f62646,0x33772dc2,0xb377adc2,0xac4433b6,0x2c44b3b6,0x315fb1ed,0x315fb1ed,0x326d30c4,0x326d30c4,0xaf32b325,0x2f323325,0x32c2b048,0xb2c23048,
0x3400,0x3400,0x264633f6,0x264633f6,0x33ff9e48,0xb3ff1e48,0x33f1a7d6,0xb3f127d6,0xa248b3fe,0xa248b3fe,0xa8b2b3ea,0xa8b2b3ea,0xb3fa24b5,0x33faa4b5,0xb3e22979,0x33e2a979,
0x3400,0x3400,0x33f6a646,0x33f6a646,0x3350ae7c,0xb3502e7c,0xafe3b2f6,0x2fe332f6,0xb1edb15f,0xb1edb15f,0xb0c4326d,0xb0c4326d,0xad053399,0x2d05b399,0x33ce2b03,0xb3ceab03,
0x3400,0x3400,0xa646b3f6,0xa646b3f6,0x3184b1cb,0xb18431cb,0xb0ec324f,0x30ecb24f,0xb3fe2248,0xb3fe2248,0x33eaa8b2,0x33eaa8b2,0x320f313a,0xb20fb13a,0xb28ab09b,0x328a309b,
0x3400,0x3400,0xb3f62646,0xb3f62646,0x2dc2b377,0xadc23377,0x33b62c44,0xb3b6ac44,0xb15f31ed,0xb15f31ed,0xb26db0c4,0xb26db0c4,0x3325af32,0xb3252f32,0x304832c2,0xb048b2c2,
0x2a3e33d9,0x2a3e33d9,0x2ca533a8,0x2ca533a8,0x2b0333ce,0xab03b3ce,0x2d053399,0xad05b399,0x2bc633c3,0x2bc633c3,0x2d643388,0x2d643388,0x2c4433b6,0xac44b3b6,0x2dc23377,0xadc2b377,
0xaa3eb3d9,0xaa3eb3d9,0xb3a82ca5,0xb3a82ca5,0xb09bb28a,0x309b328a,0xb20f313a,0x320fb13a,0xb2ddb01d,0xb2ddb01d,0xaed7333b,0xaed7333b,0xb3f1a7d6,0x33f127d6,0x9e4833ff,0x1e48b3ff,
0x2a3e33d9,0x2a3e33d9,0xaca5b3a8,0xaca5b3a8,0x32c23048,0xb2c2b048,0xb325af32,0x33252f32,0x33c3abc6,0x33c3abc6,0xb3882d64,0xb3882d64,0x2fe3b2f6,0xafe332f6,0xae7c3350,0x2e7cb350,
0xaa3eb3d9,0xaa3eb3d9,0x33a8aca5,0x33a8aca5,0xb3e2a979,0x33e22979,0x24b5b3fa,0xa4b533fa,0xb01d32dd,0xb01d32dd,0xb33baed7,0xb33baed7,0x30ec324f,0xb0ecb24f,0xb1cb3184,0x31cbb184,
0x2a3e33d9,0x2a3e33d9,0x2ca533a8,0x2ca533a8,0x33ceab03,0xb3ce2b03,0x3399ad05,0xb3992d05,0xabc6b3c3,0xabc6b3c3,0xad64b388,0xad64b388,0xb3b62c44,0x33b6ac44,0xb3772dc2,0x3377adc2,
0xaa3eb3d9,0xaa3eb3d9,0xb3a82ca5,0xb3a82ca5,0xb28a309b,0x328ab09b,0x313a320f,0xb13ab20f,0x32dd301d,0x32dd301d,0x2ed7b33b,0x2ed7b33b,0x27d6b3f1,0xa7d633f1,0xb3ff9e48,0x33ff1e48,
0x2a3e33d9,0x2a3e33d9,0xaca5b3a8,0xaca5b3a8,0x3048b2c2,0xb04832c2,0xaf323325,0x2f32b325,0xb3c32bc6,0xb3c32bc6,0x3388ad64,0x3388ad64,0x32f62fe3,0xb2f6afe3,0xb350ae7c,0x33502e7c,
0xaa3eb3d9,0xaa3eb3d9,0x33a8aca5,0x33a8aca5,0xa97933e2,0x2979b3e2,0xb3faa4b5,0x33fa24b5,0x301db2dd,0x301db2dd,0x333b2ed7,0x333b2ed7,0xb24f30ec,0x324fb0ec,0xb184b1cb,0x318431cb,
0x34000000,0x34000000,0x33f6a646,0x33f6a646,0x33ff9e48,0xb3ff1e48,0x33f1a7d6,0xb3f127d6,0x33fea248,0x33fea248,0x33eaa8b2,0x33eaa8b2,0x33faa4b5,0xb3fa24b5,0x33e2a979,0xb3e22979,
0x34000000,0x34000000,0xa646b3f6,0xa646b3f6,0x3350ae7c,0xb3502e7c,0xafe3b2f6,0x2fe332f6,0x315fb1ed,0x315fb1ed,0xb26db0c4,0xb26db0c4,0x2d05b399,0xad053399,0xb3ceab03,0x33ce2b03,
0x34000000,0x34000000,0xb3f62646,0xb3f62646,0x3184b1cb,0xb18431cb,0xb0ec324f,0x30ecb24f,0xa248b3fe,0xa248b3fe,0x28b233ea,0x28b233ea,0xb20fb13a,0x320f313a,0x328a309b,0xb28ab09b,
0x34000000,0x34000000,0x264633f6,0x264633f6,0x2dc2b377,0xadc23377,0x33b62c44,0xb3b6ac44,0xb1edb15f,0xb1edb15f,0x30c4b26d,0x30c4b26d,0xb3252f32,0x3325af32,0xb048b2c2,0x304832c2,
0x34000000,0x34000000,0x33f6a646,0x33f6a646,0x9e48b3ff,0x1e4833ff,0xa7d6b3f1,0x27d633f1,0xb3fe2248,0xb3fe2248,0xb3ea28b2,0xb3ea28b2,0x24b533fa,0xa4b5b3fa,0x297933e2,0xa979b3e2,
0x34000000,0x34000000,0xa646b3f6,0xa646b3f6,0xae7cb350,0x2e7c3350,0xb2f62fe3,0x32f6afe3,0xb15f31ed,0xb15f31ed,0x326d30c4,0x326d30c4,0x33992d05,0xb399ad05,0x2b03b3ce,0xab0333ce,
0x34000000,0x34000000,0xb3f62646,0xb3f62646,0xb1cbb184,0x31cb3184,0x324f30ec,0xb24fb0ec,0x224833fe,0x224833fe,0xa8b2b3ea,0xa8b2b3ea,0x313ab20f,0xb13a320f,0xb09b328a,0x309bb28a,
0x34000000,0x34000000,0x264633f6,0x264633f6,0xb377adc2,0x33772dc2,0x2c44b3b6,0xac4433b6,0x31ed315f,0x31ed315f,0xb0c4326d,0xb0c4326d,0xaf32b325,0x2f323325,0x32c2b048,0xb2c23048,
0x33d9aa3e,0x33d9aa3e,0x33a8aca5,0x33a8aca5,0x33ceab03,0xb3ce2b03,0x3399ad05,0xb3992d05,0x33c3abc6,0x33c3abc6,0x3388ad64,0x3388ad64,0x33b6ac44,0xb3b62c44,0x3377adc2,0xb3772dc2,
0xb3d92a3e,0xb3d92a3e,0x2ca533a8,0x2ca533a8,0xb28a309b,0x328ab09b,0x313a320f,0xb13ab20f,0xb01d32dd,0xb01d32dd,0x333b2ed7,0x333b2ed7,0xa7d633f1,0x27d6b3f1,0x33ff1e48,0xb3ff9e48,
0x33d9aa3e,0x33d9aa3e,0xb3a82ca5,0xb3a82ca5,0x3048b2c2,0xb04832c2,0xaf323325,0x2f32b325,0xabc6b3c3,0xabc6b3c3,0x2d643388,0x2d643388,0xb2f6afe3,0x32f62fe3,0x33502e7c,0xb350ae7c,
0xb3d92a3e,0xb3d92a3e,0xaca5b3a8,0xaca5b3a8,0xa97933e2,0x2979b3e2,0xb3faa4b5,0x33fa24b5,0x32dd301d,0x32dd301d,0xaed7333b,0xaed7333b,0x324fb0ec,0xb24f30ec,0x318431cb,0xb184b1cb,
0x33d9aa3e,0x33d9aa3e,0x33a8aca5,0x33a8aca5,0xab03b3ce,0x2b0333ce,0xad05b399,0x2d053399,0xb3c32bc6,0xb3c32bc6,0xb3882d64,0xb3882d64,0x2c4433b6,0xac44b3b6,0x2dc23377,0xadc2b377,
0xb3d92a3e,0xb3d92a3e,0x2ca533a8,0x2ca533a8,0x309b328a,0xb09bb28a,0x320fb13a,0xb20f313a,0x301db2dd,0x301db2dd,0xb33baed7,0xb33baed7,0xb3f1a7d6,0x33f127d6,0x9e4833ff,0x1e48b3ff,
0x33d9aa3e,0x33d9aa3e,0xb3a82ca5,0xb3a82ca5,0xb2c2b048,0x32c23048,0x33252f32,0xb325af32,0x2bc633c3,0x2bc633c3,0xad64b388,0xad64b388,0x2fe3b2f6,0xafe332f6,0xae7c3350,0x2e7cb350,
0xb3d92a3e,0xb3d92a3e,0xaca5b3a8,0xaca5b3a8,0x33e22979,0xb3e2a979,0xa4b533fa,0x24b5b3fa,0xb2ddb01d,0xb2ddb01d,0x2ed7b33b,0x2ed7b33b,0x30ec324f,0xb0ecb24f,0xb1cb3184,0x31cbb184,
0x35a835a8,0x353835a8,0x14710000,0x305d0000,0x35a835a8,0x303c33f3,0x1aaa1871,0x353f3406,0x35a835a8,0xb07d9c71,0x1d8e1c71,0x353135a8,0x35a835a8,0xb546b413,0x1fc61eaa,0x301b33da,
0x35a635a8,0x351b35a8,0x24b80000,0x30de0000,0x359635a0,0x2d4c3320,0x2b0d28b6,0x35803465,0x35773589,0xb2e1acb0,0x2dd62cb0,0x347e3589,0x35493562,0xb5a8b50a,0x300a2ef7,0x20ff3126,
0x35a135a8,0x34fb35a8,0x28930000,0x315d0000,0x3566358b,0x2805323a,0x2ec42c8d,0x35a234b9,0x34f33533,0xb46db075,0x317c3075,0x330b3533,0x344b34a5,0xb560b591,0x335d3275,0xaf082c01,
0x359835a8,0x34d835a8,0x2ac70000,0x31d90000,0x35173567,0xa5463146,0x30ee2eb3,0x35a63501,0x342234aa,0xb526b267,0x33ba3267,0x30ae34aa,0x319b3304,0xb478b59e,0x34ea3470,0xb2efa944,
0x358b35a8,0x34b235a8,0x2c7c0000,0x32500000,0x34ad3536,0xac9e3044,0x325f3065,0x358a353d,0x322433e7,0xb590b40c,0x34c0340c,0x2c1333e7,0x2be03023,0xb215b52f,0x35923544,0xb4c5b085,
0x357c35a8,0x348935a8,0x2d910000,0x32c40000,0x342834f9,0xafd22e6f,0x33ad3165,0x354f356c,0x2f4c322b,0xb5a5b4be,0x355b34be,0xa5d4322b,0xab9a2736,0xad07b44e,0x359435a4,0xb584b356,
0x356935a8,0x345d35a8,0x2ea30000,0x33340000,0x331934af,0xb16d2c47,0x34683258,0x34f7358e,0x277d3033,0xb563b541,0x35a33541,0xaee63033,0xb18cacd2,0x2967b21d,0x34ee3587,0xb59eb4c3,
0x355235a8,0x342e35a8,0x2fb00000,0x33a00000,0x31ba345a,0xb2d32829,0x34e1333b,0x348335a2,0xab532c24,0xb4cfb590,0x35953590,0xb1f72c24,0xb446b184,0x310eae2b,0x336b34f0,0xb510b571,
0x3c003c00,0x0,0x0,0x3c003c00,0x3c003c00,0x0,0x0,0x3c003c00,0x3c003c00,0x0,0x0,0x3c003c00,0x3c003c00,0x0,0x0,0x3c003c00,
0x39a83c00,0x39a80000,0xb9a80000,0x39a83c00,0xb9a80000,0x39a83c00,0xb9a8bc00,0xb9a80000,0xb9a8bc00,0xb9a80000,0x39a80000,0xb9a8bc00,0x39a80000,0xb9a8bc00,0x39a83c00,0x39a80000,
0x3c00,0x3c000000,0xbc000000,0x3c00,0xbc00,0xbc000000,0x3c000000,0xbc00,0x3c00,0x3c000000,0xbc000000,0x3c00,0xbc00,0xbc000000,0x3c000000,0xbc00,
0xb9a83c00,0x39a80000,0xb9a80000,0xb9a83c00,0x39a80000,0x39a8bc00,0xb9a83c00,0x39a80000,0x39a8bc00,0xb9a80000,0x39a80000,0x39a8bc00,0xb9a80000,0xb9a83c00,0x39a8bc00,0xb9a80000,
0xbc003c00,0x0,0x0,0xbc003c00,0xbc003c00,0x0,0x0,0xbc003c00,0xbc003c00,0x0,0x0,0xbc003c00,0xbc003c00,0x0,0x0,0xbc003c00,
0xb9a83c00,0xb9a80000,0x39a80000,0xb9a83c00,0x39a80000,0xb9a83c00,0x39a8bc00,0x39a80000,0x39a8bc00,0x39a80000,0xb9a80000,0x39a8bc00,0xb9a80000,0x39a8bc00,0xb9a83c00,0xb9a80000,
0x3c00,0xbc000000,0x3c000000,0x3c00,0xbc00,0x3c000000,0xbc000000,0xbc00,0x3c00,0xbc000000,0x3c000000,0x3c00,0xbc00,0x3c000000,0xbc000000,0xbc00,
0x39a83c00,0xb9a80000,0x39a80000,0x39a83c00,0xb9a80000,0xb9a8bc00,0x39a83c00,0xb9a80000,0xb9a8bc00,0x39a80000,0xb9a80000,0xb9a8bc00,0x39a80000,0x39a83c00,0xb9a8bc00,0x39a80000,
0x3c003c00,0x0,0x0,0x3c003c00,0x3c003c00,0x0,0x0,0x3c003c00,0x3c003c00,0x0,0x0,0x3c003c00,0x3c003c00,0x0,0x0,0x3c003c00,
0x39a83c00,0x39a80000,0xb9a80000,0x39a83c00,0xb9a80000,0x39a83c00,0xb9a8bc00,0xb9a80000,0xb9a8bc00,0xb9a80000,0x39a80000,0xb9a8bc00,0x39a80000,0xb9a8bc00,0x39a83c00,0x39a80000,
0x3c00,0x3c000000,0xbc000000,0x3c00,0xbc00,0xbc000000,0x3c000000,0xbc00,0x3c00,0x3c000000,0xbc000000,0x3c00,0xbc00,0xbc000000,0x3c000000,0xbc00,
0xb9a83c00,0x39a80000,0xb9a80000,0xb9a83c00,0x39a80000,0x39a8bc00,0xb9a83c00,0x39a80000,0x39a8bc00,0xb9a80000,0x39a80000,0x39a8bc00,0xb9a80000,0xb9a83c00,0x39a8bc00,0xb9a80000,
0xbc003c00,0x0,0x0,0xbc003c00,0xbc003c00,0x0,0x0,0xbc003c00,0xbc003c00,0x0,0x0,0xbc003c00,0xbc003c00,0x0,0x0,0xbc003c00,
0xb9a83c00,0xb9a80000,0x39a80000,0xb9a83c00,0x39a80000,0xb9a83c00,0x39a8bc00,0x39a80000,0x39a8bc00,0x39a80000,0xb9a80000,0x39a8bc00,0xb9a80000,0x39a8bc00,0xb9a83c00,0xb9a80000,
0x3c00,0xbc000000,0x3c000000,0x3c00,0xbc00,0x3c000000,0xbc000000,0xbc00,0x3c00,0xbc000000,0x3c000000,0x3c00,0xbc00,0x3c000000,0xbc000000,0xbc00,
0x39a83c00,0xb9a80000,0x39a80000,0x39a83c00,0xb9a80000,0xb9a8bc00,0x39a83c00,0xb9a80000,0xb9a8bc00,0x39a80000,0xb9a80000,0xb9a8bc00,0x39a80000,0x39a83c00,0xb9a8bc00,0x39a80000,
0x35a835a8,0x35a835a8,0x0,0x0,0x35a835a8,0x35a835a8,0x0,0x0,0x35a835a8,0x35a835a8,0x0,0x0,0x35a835a8,0x35a835a8,0x0,0x0,
0x35a635a8,0x351b3538,0x24b81471,0x30de305d,0x359835a1,0x34d834fb,0x2ac72893,0x31d9315d,0x357c358b,0x348934b2,0x2d912c7c,0x32c43250,0x35523569,0x342e345d,0x2fb02ea3,0x33a03334,
0x35a035a8,0x332033f3,0x28b61871,0x34653406,0x3567358b,0x3146323a,0x2eb32c8d,0x350134b9,0x34f93536,0x2e6f3044,0x31653065,0x356c353d,0x345a34af,0x28292c47,0x333b3258,0x35a2358e,
0x359635a8,0x2d4c303c,0x2b0d1aaa,0x3580353f,0x35173566,0xa5462805,0x30ee2ec4,0x35a635a2,0x342834ad,0xafd2ac9e,0x33ad325f,0x354f358a,0x31ba3319,0xb2d3b16d,0x34e13468,0x348334f7,
0x358935a8,0xacb09c71,0x2cb01c71,0x358935a8,0x34aa3533,0xb267b075,0x32673075,0x34aa3533,0x322b33e7,0xb4beb40c,0x34be340c,0x322b33e7,0x2c243033,0xb590b541,0x35903541,0x2c243033,
0x357735a8,0xb2e1b07d,0x2dd61d8e,0x347e3531,0x342234f3,0xb526b46d,0x33ba317c,0x30ae330b,0x2f4c3224,0xb5a5b590,0x355b34c0,0xa5d42c13,0xab53277d,0xb4cfb563,0x359535a3,0xb1f7aee6,
0x356235a8,0xb50ab413,0x2ef71eaa,0x312633da,0x330434a5,0xb59eb591,0x34703275,0xa9442c01,0x27363023,0xb44eb52f,0x35a43544,0xb356b085,0xb184acd2,0xae2bb21d,0x34f03587,0xb571b4c3,
0x354935a8,0xb5a8b546,0x300a1fc6,0x20ff301b,0x319b344b,0xb478b560,0x34ea335d,0xb2efaf08,0xab9a2be0,0xad07b215,0x35943592,0xb584b4c5,0xb446b18c,0x310e2967,0x336b34ee,0xb510b59e,
0x34003400,0x34003400,0x0,0x0,0x34003400,0x34003400,0x0,0x0,0x34003400,0x34003400,0x0,0x0,0x34003400,0x34003400,0x0,0x0,
0x0,0x0,0x34003400,0x34003400,0x0,0x0,0x34003400,0x34003400,0x0,0x0,0x34003400,0x34003400,0x0,0x0,0x34003400,0x34003400,
0x335033ff,0xb350b3ff,0xae7c9e48,0x2e7c1e48,0x2dc23184,0xadc2b184,0xb377b1cb,0x337731cb,0xae7c9e48,0x2e7c1e48,0xb350b3ff,0x335033ff,0xb377b1cb,0x337731cb,0xadc2b184,0x2dc23184,
0x2e7c1e48,0xae7c9e48,0x335033ff,0xb350b3ff,0x337731cb,0xb377b1cb,0x2dc23184,0xadc2b184,0x335033ff,0xb350b3ff,0xae7c9e48,0x2e7c1e48,0x2dc23184,0xadc2b184,0xb377b1cb,0x337731cb,
0x315f33fe,0x315f33fe,0xb1eda248,0xb1eda248,0xb1eda248,0xb1eda248,0xb15fb3fe,0xb15fb3fe,0xb15fb3fe,0xb15fb3fe,0x31ed2248,0x31ed2248,0x31ed2248,0x31ed2248,0x315f33fe,0x315f33fe,
0x31ed2248,0x31ed2248,0x315f33fe,0x315f33fe,0x315f33fe,0x315f33fe,0xb1eda248,0xb1eda248,0xb1eda248,0xb1eda248,0xb15fb3fe,0xb15fb3fe,0xb15fb3fe,0xb15fb3fe,0x31ed2248,0x31ed2248,
0x2d0533fa,0xad05b3fa,0xb399a4b5,0x339924b5,0xb325b20f,0x3325320f,0x2f32b13a,0xaf32313a,0x339924b5,0xb399a4b5,0x2d0533fa,0xad05b3fa,0xaf32313a,0x2f32b13a,0xb325b20f,0x3325320f,
0x339924b5,0xb399a4b5,0x2d0533fa,0xad05b3fa,0xaf32313a,0x2f32b13a,0xb325b20f,0x3325320f,0xad05b3fa,0x2d0533fa,0x339924b5,0xb399a4b5,0x3325320f,0xb325b20f,0xaf32313a,0x2f32b13a,
0xa64633f6,0xa64633f6,0xb3f6a646,0xb3f6a646,0x2646b3f6,0x2646b3f6,0x33f62646,0x33f62646,0xa64633f6,0xa64633f6,0xb3f6a646,0xb3f6a646,0x2646b3f6,0x2646b3f6,0x33f62646,0x33f62646,
0x33f62646,0x33f62646,0xa64633f6,0xa64633f6,0xb3f6a646,0xb3f6a646,0x2646b3f6,0x2646b3f6,0x33f62646,0x33f62646,0xa64633f6,0xa64633f6,0xb3f6a646,0xb3f6a646,0x2646b3f6,0x2646b3f6,
0xafe333f1,0x2fe3b3f1,0xb2f6a7d6,0x32f627d6,0x33b6b0ec,0xb3b630ec,0x2c44324f,0xac44b24f,0xb2f6a7d6,0x32f627d6,0x2fe3b3f1,0xafe333f1,0x2c44324f,0xac44b24f,0xb3b630ec,0x33b6b0ec,
0x32f627d6,0xb2f6a7d6,0xafe333f1,0x2fe3b3f1,0xac44b24f,0x2c44324f,0x33b6b0ec,0xb3b630ec,0xafe333f1,0x2fe3b3f1,0xb2f6a7d6,0x32f627d6,0x33b6b0ec,0xb3b630ec,0x2c44324f,0xac44b24f,
0xb26d33ea,0xb26d33ea,0xb0c4a8b2,0xb0c4a8b2,0x30c428b2,0x30c428b2,0xb26d33ea,0xb26d33ea,0x326db3ea,0x326db3ea,0x30c428b2,0x30c428b2,0xb0c4a8b2,0xb0c4a8b2,0x326db3ea,0x326db3ea,
0x30c428b2,0x30c428b2,0xb26d33ea,0xb26d33ea,0x326db3ea,0x326db3ea,0x30c428b2,0x30c428b2,0xb0c4a8b2,0xb0c4a8b2,0x326db3ea,0x326db3ea,0xb26d33ea,0xb26d33ea,0xb0c4a8b2,0xb0c4a8b2,
0xb3ce33e2,0x33ceb3e2,0xab03a979,0x2b032979,0xb048328a,0x3048b28a,0xb2c2309b,0x32c2b09b,0x2b032979,0xab03a979,0xb3ce33e2,0x33ceb3e2,0x32c2b09b,0xb2c2309b,0xb048328a,0x3048b28a,
0x2b032979,0xab03a979,0xb3ce33e2,0x33ceb3e2,0x32c2b09b,0xb2c2309b,0xb048328a,0x3048b28a,0x33ceb3e2,0xb3ce33e2,0x2b032979,0xab03a979,0x3048b28a,0xb048328a,0x32c2b09b,0xb2c2309b,
0xb3d933d9,0xb3d933d9,0x2a3eaa3e,0x2a3eaa3e,0xb3d933d9,0xb3d933d9,0x2a3eaa3e,0x2a3eaa3e,0xb3d933d9,0xb3d933d9,0x2a3eaa3e,0x2a3eaa3e,0xb3d933d9,0xb3d933d9,0x2a3eaa3e,0x2a3eaa3e,
0xaa3e2a3e,0xaa3e2a3e,0xb3d933d9,0xb3d933d9,0xaa3e2a3e,0xaa3e2a3e,0xb3d933d9,0xb3d933d9,0xaa3e2a3e,0xaa3e2a3e,0xb3d933d9,0xb3d933d9,0xaa3e2a3e,0xaa3e2a3e,0xb3d933d9,0xb3d933d9,
0xb28a33ce,0x328ab3ce,0x309bab03,0xb09b2b03,0xa9793048,0x2979b048,0x33e2b2c2,0xb3e232c2,0x309bab03,0xb09b2b03,0x328ab3ce,0xb28a33ce,0x33e2b2c2,0xb3e232c2,0x2979b048,0xa9793048,
0xb09b2b03,0x309bab03,0xb28a33ce,0x328ab3ce,0xb3e232c2,0x33e2b2c2,0xa9793048,0x2979b048,0xb28a33ce,0x328ab3ce,0x309bab03,0xb09b2b03,0xa9793048,0x2979b048,0x33e2b2c2,0xb3e232c2,
0xb01d33c3,0xb01d33c3,0x32ddabc6,0x32ddabc6,0x32ddabc6,0x32ddabc6,0x301db3c3,0x301db3c3,0x301db3c3,0x301db3c3,0xb2dd2bc6,0xb2dd2bc6,0xb2dd2bc6,0xb2dd2bc6,0xb01d33c3,0xb01d33c3,
0xb2dd2bc6,0xb2dd2bc6,0xb01d33c3,0xb01d33c3,0xb01d33c3,0xb01d33c3,0x32ddabc6,0x32ddabc6,0x32ddabc6,0x32ddabc6,0x301db3c3,0x301db3c3,0x301db3c3,0x301db3c3,0xb2dd2bc6,0xb2dd2bc6,
0xa7d633b6,0x27d6b3b6,0x33f1ac44,0xb3f12c44,0x324fb2f6,0xb24f32f6,0xb0ecafe3,0x30ec2fe3,0xb3f12c44,0x33f1ac44,0xa7d633b6,0x27d6b3b6,0x30ec2fe3,0xb0ecafe3,0x324fb2f6,0xb24f32f6,
0xb3f12c44,0x33f1ac44,0xa7d633b6,0x27d6b3b6,0x30ec2fe3,0xb0ecafe3,0x324fb2f6,0xb24f32f6,0x27d6b3b6,0xa7d633b6,0xb3f12c44,0x33f1ac44,0xb24f32f6,0x324fb2f6,0x30ec2fe3,0xb0ecafe3,
0x2ca533a8,0x2ca533a8,0x33a8aca5,0x33a8aca5,0xaca5b3a8,0xaca5b3a8,0xb3a82ca5,0xb3a82ca5,0x2ca533a8,0x2ca533a8,0x33a8aca5,0x33a8aca5,0xaca5b3a8,0xaca5b3a8,0xb3a82ca5,0xb3a82ca5,
0xb3a82ca5,0xb3a82ca5,0x2ca533a8,0x2ca533a8,0x33a8aca5,0x33a8aca5,0xaca5b3a8,0xaca5b3a8,0xb3a82ca5,0xb3a82ca5,0x2ca533a8,0x2ca533a8,0x33a8aca5,0x33a8aca5,0xaca5b3a8,0xaca5b3a8,
0x313a3399,0xb13ab399,0x320fad05,0xb20f2d05,0xb3faaf32,0x33fa2f32,0xa4b53325,0x24b5b325,0x320fad05,0xb20f2d05,0xb13ab399,0x313a3399,0xa4b53325,0x24b5b325,0x33fa2f32,0xb3faaf32,
0xb20f2d05,0x320fad05,0x313a3399,0xb13ab399,0x24b5b325,0xa4b53325,0xb3faaf32,0x33fa2f32,0x313a3399,0xb13ab399,0x320fad05,0xb20f2d05,0xb3faaf32,0x33fa2f32,0xa4b53325,0x24b5b325,
0x333b3388,0x333b3388,0x2ed7ad64,0x2ed7ad64,0xaed72d64,0xaed72d64,0x333b3388,0x333b3388,0xb33bb388,0xb33bb388,0xaed72d64,0xaed72d64,0x2ed7ad64,0x2ed7ad64,0xb33bb388,0xb33bb388,
0xaed72d64,0xaed72d64,0x333b3388,0x333b3388,0xb33bb388,0xb33bb388,0xaed72d64,0xaed72d64,0x2ed7ad64,0x2ed7ad64,0xb33bb388,0xb33bb388,0x333b3388,0x333b3388,0x2ed7ad64,0x2ed7ad64,
0x33ff3377,0xb3ffb377,0x1e48adc2,0x9e482dc2,0x31843350,0xb184b350,0x31cb2e7c,0xb1cbae7c,0x9e482dc2,0x1e48adc2,0x33ff3377,0xb3ffb377,0xb1cbae7c,0x31cb2e7c,0x31843350,0xb184b350,
0x9e482dc2,0x1e48adc2,0x33ff3377,0xb3ffb377,0xb1cbae7c,0x31cb2e7c,0x31843350,0xb184b350,0xb3ffb377,0x33ff3377,0x9e482dc2,0x1e48adc2,0xb184b350,0x31843350,0xb1cbae7c,0x31cb2e7c,
0x3400,0x3400,0x2a3e33d9,0x2a3e33d9,0x224833fe,0xa248b3fe,0x2bc633c3,0xabc6b3c3,0x264633f6,0x264633f6,0x2ca533a8,0x2ca533a8,0x28b233ea,0xa8b2b3ea,0x2d643388,0xad64b388,
0x3400,0x3400,0x33d9aa3e,0x33d9aa3e,0x2ed7333b,0xaed7b33b,0x326db0c4,0xb26d30c4,0x322f3113,0x322f3113,0x2f8bb30e,0x2f8bb30e,0x33c32bc6,0xb3c3abc6,0x2248b3fe,0xa24833fe,
0x3400,0x3400,0xaa3eb3d9,0xaa3eb3d9,0x31ed315f,0xb1edb15f,0xb2ddb01d,0x32dd301d,0x33f6a646,0x33f6a646,0xb3a82ca5,0xb3a82ca5,0x30c4b26d,0xb0c4326d,0xaed7333b,0x2ed7b33b,
0x3400,0x3400,0xb3d92a3e,0xb3d92a3e,0x33882d64,0xb388ad64,0xa8b233ea,0x28b2b3ea,0x3113b22f,0x3113b22f,0x330e2f8b,0x330e2f8b,0xb01db2dd,0x301d32dd,0x31edb15f,0xb1ed315f,
0x3400,0x3400,0x2a3e33d9,0x2a3e33d9,0x33fea248,0xb3fe2248,0x33c3abc6,0xb3c32bc6,0xa646b3f6,0xa646b3f6,0xaca5b3a8,0xaca5b3a8,0xb3ea28b2,0x33eaa8b2,0xb3882d64,0x3388ad64,
0x3400,0x3400,0x33d9aa3e,0x33d9aa3e,0x333baed7,0xb33b2ed7,0xb0c4b26d,0x30c4326d,0xb22fb113,0xb22fb113,0xaf8b330e,0xaf8b330e,0xabc633c3,0x2bc6b3c3,0x33fe2248,0xb3fea248,
0x3400,0x3400,0xaa3eb3d9,0xaa3eb3d9,0x315fb1ed,0xb15f31ed,0xb01d32dd,0x301db2dd,0xb3f62646,0xb3f62646,0x33a8aca5,0x33a8aca5,0x326d30c4,0xb26db0c4,0xb33baed7,0x333b2ed7,
0x3400,0x3400,0xb3d92a3e,0xb3d92a3e,0x2d64b388,0xad643388,0x33ea28b2,0xb3eaa8b2,0xb113322f,0xb113322f,0xb30eaf8b,0xb30eaf8b,0x32ddb01d,0xb2dd301d,0x315f31ed,0xb15fb1ed,
0x2e1f3364,0x2e1f3364,0x307232a7,0x307232a7,0x2ed7333b,0xaed7b33b,0x30c4326d,0xb0c4b26d,0x2f8b330e,0x2f8b330e,0x3113322f,0x3113322f,0x301d32dd,0xb01db2dd,0x315f31ed,0xb15fb1ed,
0xae1fb364,0xae1fb364,0xb2a73072,0xb2a73072,0xb1edb15f,0x31ed315f,0xb01d32dd,0x301db2dd,0xb3a8aca5,0xb3a8aca5,0xa64633f6,0xa64633f6,0xb3ea28b2,0x33eaa8b2,0x2d643388,0xad64b388,
0x2e1f3364,0x2e1f3364,0xb072b2a7,0xb072b2a7,0x33882d64,0xb388ad64,0xb3eaa8b2,0x33ea28b2,0x330eaf8b,0x330eaf8b,0xb22f3113,0xb22f3113,0x2bc6b3c3,0xabc633c3,0xa24833fe,0x2248b3fe,
0xae1fb364,0xae1fb364,0x32a7b072,0x32a7b072,0xb3fe2248,0x33fea248,0xabc6b3c3,0x2bc633c3,0xaca533a8,0xaca533a8,0xb3f6a646,0xb3f6a646,0x326d30c4,0xb26db0c4,0xaed7333b,0x2ed7b33b,
0x2e1f3364,0x2e1f3364,0x307232a7,0x307232a7,0x333baed7,0xb33b2ed7,0x326db0c4,0xb26d30c4,0xaf8bb30e,0xaf8bb30e,0xb113b22f,0xb113b22f,0xb2dd301d,0x32ddb01d,0xb1ed315f,0x31edb15f,
0xae1fb364,0xae1fb364,0xb2a73072,0xb2a73072,0xb15f31ed,0x315fb1ed,0x32dd301d,0xb2ddb01d,0x33a82ca5,0x33a82ca5,0x2646b3f6,0x2646b3f6,0xa8b2b3ea,0x28b233ea,0xb3882d64,0x3388ad64,
0x2e1f3364,0x2e1f3364,0xb072b2a7,0xb072b2a7,0x2d64b388,0xad643388,0xa8b233ea,0x28b2b3ea,0xb30e2f8b,0xb30e2f8b,0x322fb113,0x322fb113,0x33c32bc6,0xb3c3abc6,0xb3fea248,0x33fe2248,
0xae1fb364,0xae1fb364,0x32a7b072,0x32a7b072,0x224833fe,0xa248b3fe,0xb3c32bc6,0x33c3abc6,0x2ca5b3a8,0x2ca5b3a8,0x33f62646,0x33f62646,0xb0c4326d,0x30c4b26d,0xb33baed7,0x333b2ed7,
0x34000000,0x34000000,0x33d9aa3e,0x33d9aa3e,0x33fea248,0xb3fe2248,0x33c3abc6,0xb3c32bc6,0x33f6a646,0x33f6a646,0x33a8aca5,0x33a8aca5,0x33eaa8b2,0xb3ea28b2,0x3388ad64,0xb3882d64,
0x34000000,0x34000000,0xaa3eb3d9,0xaa3eb3d9,0x333baed7,0xb33b2ed7,0xb0c4b26d,0x30c4326d,0x3113b22f,0x3113b22f,0xb30eaf8b,0xb30eaf8b,0x2bc6b3c3,0xabc633c3,0xb3fea248,0x33fe2248,
0x34000000,0x34000000,0xb3d92a3e,0xb3d92a3e,0x315fb1ed,0xb15f31ed,0xb01d32dd,0x301db2dd,0xa646b3f6,0xa646b3f6,0x2ca533a8,0x2ca533a8,0xb26db0c4,0x326d30c4,0x333b2ed7,0xb33baed7,
0x34000000,0x34000000,0x2a3e33d9,0x2a3e33d9,0x2d64b388,0xad643388,0x33ea28b2,0xb3eaa8b2,0xb22fb113,0xb22fb113,0x2f8bb30e,0x2f8bb30e,0xb2dd301d,0x32ddb01d,0xb15fb1ed,0x315f31ed,
0x34000000,0x34000000,0x33d9aa3e,0x33d9aa3e,0xa248b3fe,0x224833fe,0xabc6b3c3,0x2bc633c3,0xb3f62646,0xb3f62646,0xb3a82ca5,0xb3a82ca5,0x28b233ea,0xa8b2b3ea,0x2d643388,0xad64b388,
0x34000000,0x34000000,0xaa3eb3d9,0xaa3eb3d9,0xaed7b33b,0x2ed7333b,0xb26d30c4,0x326db0c4,0xb113322f,0xb113322f,0x330e2f8b,0x330e2f8b,0x33c32bc6,0xb3c3abc6,0x2248b3fe,0xa24833fe,
0x34000000,0x34000000,0xb3d92a3e,0xb3d92a3e,0xb1edb15f,0x31ed315f,0x32dd301d,0xb2ddb01d,0x264633f6,0x264633f6,0xaca5b3a8,0xaca5b3a8,0x30c4b26d,0xb0c4326d,0xaed7333b,0x2ed7b33b,
0x34000000,0x34000000,0x2a3e33d9,0x2a3e33d9,0xb388ad64,0x33882d64,0x28b2b3ea,0xa8b233ea,0x322f3113,0x322f3113,0xaf8b330e,0xaf8b330e,0xb01db2dd,0x301d32dd,0x31edb15f,0xb1ed315f,
0x3364ae1f,0x3364ae1f,0x32a7b072,0x32a7b072,0x333baed7,0xb33b2ed7,0x326db0c4,0xb26d30c4,0x330eaf8b,0x330eaf8b,0x322fb113,0x322fb113,0x32ddb01d,0xb2dd301d,0x31edb15f,0xb1ed315f,
0xb3642e1f,0xb3642e1f,0x307232a7,0x307232a7,0xb15f31ed,0x315fb1ed,0x32dd301d,0xb2ddb01d,0xaca533a8,0xaca533a8,0x33f62646,0x33f62646,0x28b233ea,0xa8b2b3ea,0x3388ad64,0xb3882d64,
0x3364ae1f,0x3364ae1f,0xb2a73072,0xb2a73072,0x2d64b388,0xad643388,0xa8b233ea,0x28b2b3ea,0xaf8bb30e,0xaf8bb30e,0x3113322f,0x3113322f,0xb3c3abc6,0x33c32bc6,0x33fe2248,0xb3fea248,
0xb3642e1f,0xb3642e1f,0xb072b2a7,0xb072b2a7,0x224833fe,0xa248b3fe,0xb3c32bc6,0x33c3abc6,0x33a82ca5,0x33a82ca5,0xa64633f6,0xa64633f6,0x30c4b26d,0xb0c4326d,0x333b2ed7,0xb33baed7,
0x3364ae1f,0x3364ae1f,0x32a7b072,0x32a7b072,0xaed7b33b,0x2ed7333b,0xb0c4b26d,0x30c4326d,0xb30e2f8b,0xb30e2f8b,0xb22f3113,0xb22f3113,0x301d32dd,0xb01db2dd,0x315f31ed,0xb15fb1ed,
0xb3642e1f,0xb3642e1f,0x307232a7,0x307232a7,0x31ed315f,0xb1edb15f,0x301db2dd,0xb01d32dd,0x2ca5b3a8,0x2ca5b3a8,0xb3f6a646,0xb3f6a646,0xb3ea28b2,0x33eaa8b2,0x2d643388,0xad64b388,
0x3364ae1f,0x3364ae1f,0xb2a73072,0xb2a73072,0xb388ad64,0x33882d64,0x33ea28b2,0xb3eaa8b2,0x2f8b330e,0x2f8b330e,0xb113b22f,0xb113b22f,0x2bc6b3c3,0xabc633c3,0xa24833fe,0x2248b3fe,
0xb3642e1f,0xb3642e1f,0xb072b2a7,0xb072b2a7,0x33fea248,0xb3fe2248,0x2bc633c3,0xabc6b3c3,0xb3a8aca5,0xb3a8aca5,0x2646b3f6,0x2646b3f6,0x326d30c4,0xb26db0c4,0xaed7333b,0x2ed7b33b,
0x35a835a8,0x353635a8,0x18710000,0x30650000,0x35a835a8,0x302333e7,0x1eaa1c71,0x3544340c,0x35a735a8,0xb0a6a071,0x218d2071,0x352835a8,0x35a735a7,0xb550b425,0x23c622aa,0x2fc133b3,
0x35a635a8,0x351935a8,0x24ff0000,0x30e60000,0x3594359f,0x2d183312,0x2b7728fd,0x3583346b,0x35713585,0xb304acf5,0x2e2b2cf5,0x34703585,0x353d3559,0xb5a8b515,0x30442f5c,0x187130f6,
0x35a035a8,0x34f935a8,0x28b60000,0x31650000,0x35623589,0x2736322b,0x2ef72cb0,0x35a434be,0x34e8352c,0xb47bb096,0x31a33096,0x32e8352c,0x34373496,0xb556b596,0x338c32a1,0xaf7e2b30,
0x359735a8,0x34d635a8,0x2aea0000,0x31e00000,0x35113565,0xa61b3136,0x31062ed5,0x35a53505,0x341334a0,0xb52fb284,0x33da3284,0x308534a0,0x316532da,0xb465b59b,0x34f93480,0xb320aa17,
0x358b35a8,0x34af35a8,0x2c8d0000,0x32580000,0x34a53533,0xacd23033,0x32753075,0x35873541,0x31fe33cd,0xb594b419,0x34cc3419,0x2b7733cd,0x2aea2fe2,0xb1e0b525,0x3597354d,0xb4d6b0b6,
0x357b35a8,0x348635a8,0x2da20000,0x32cc0000,0x341f34f5,0xb0022e4d,0x33c03175,0x354a356f,0x2ef7320e,0xb5a4b4c7,0x356234c7,0xa736320e,0xac47258d,0xac8db43d,0x358e35a5,0xb58bb37f,
0x356735a8,0x345a35a8,0x2eb30000,0x333b0000,0x330434aa,0xb1842c24,0x34703267,0x34f03590,0x261b3012,0xb55cb547,0x35a53547,0xaf3b3012,0xb1c2ad3a,0x2a5eb1ef,0x34df3581,0xb59ab4d1,
0x355035a8,0x342b35a8,0x2fc10000,0x33a60000,0x31a33454,0xb2e827c4,0x34e83349,0x347b35a3,0xac012bbd,0xb4c3b593,0x35913593,0xb21d2bbd,0xb45ab1b2,0x3146adc4,0x333b34e3,0xb501b578,
0x3c003c00,0x0,0x0,0x3c003c00,0x3c003c00,0x0,0x0,0x3c003c00,0x3c003c00,0x0,0x0,0x3c003c00,0x3c003c00,0x0,0x0,0x3c003c00,
0x39a83c00,0x39a80000,0xb9a80000,0x39a83c00,0xb9a80000,0x39a83c00,0xb9a8bc00,0xb9a80000,0xb9a8bc00,0xb9a80000,0x39a80000,0xb9a8bc00,0x39a80000,0xb9a8bc00,0x39a83c00,0x39a80000,
0x3c00,0x3c000000,0xbc000000,0x3c00,0xbc00,0xbc000000,0x3c000000,0xbc00,0x3c00,0x3c000000,0xbc000000,0x3c00,0xbc00,0xbc000000,0x3c000000,0xbc00,
0xb9a83c00,0x39a80000,0xb9a80000,0xb9a83c00,0x39a80000,0x39a8bc00,0xb9a83c00,0x39a80000,0x39a8bc00,0xb9a80000,0x39a80000,0x39a8bc00,0xb9a80000,0xb9a83c00,0x39a8bc00,0xb9a80000,
0xbc003c00,0x0,0x0,0xbc003c00,0xbc003c00,0x0,0x0,0xbc003c00,0xbc003c00,0x0,0x0,0xbc003c00,0xbc003c00,0x0,0x0,0xbc003c00,
0xb9a83c00,0xb9a80000,0x39a80000,0xb9a83c00,0x39a80000,0xb9a83c00,0x39a8bc00,0x39a80000,0x39a8bc00,0x39a80000,0xb9a80000,0x39a8bc00,0xb9a80000,0x39a8bc00,0xb9a83c00,0xb9a80000,
0x3c00,0xbc000000,0x3c000000,0x3c00,0xbc00,0x3c000000,0xbc000000,0xbc00,0x3c00,0xbc000000,0x3c000000,0x3c00,0xbc00,0x3c000000,0xbc000000,0xbc00,
0x39a83c00,0xb9a80000,0x39a80000,0x39a83c00,0xb9a80000,0xb9a8bc00,0x39a83c00,0xb9a80000,0xb9a8bc00,0x39a80000,0xb9a80000,0xb9a8bc00,0x39a80000,0x39a83c00,0xb9a8bc00,0x39a80000,
0x3c003c00,0x0,0x0,0x3c003c00,0x3c003c00,0x0,0x0,0x3c003c00,0x3c003c00,0x0,0x0,0x3c003c00,0x3c003c00,0x0,0x0,0x3c003c00,
0x39a83c00,0x39a80000,0xb9a80000,0x39a83c00,0xb9a80000,0x39a83c00,0xb9a8bc00,0xb9a80000,0xb9a8bc00,0xb9a80000,0x39a80000,0xb9a8bc00,0x39a80000,0xb9a8bc00,0x39a83c00,0x39a80000,
0x3c00,0x3c000000,0xbc000000,0x3c00,0xbc00,0xbc000000,0x3c000000,0xbc00,0x3c00,0x3c000000,0xbc000000,0x3c00,0xbc00,0xbc000000,0x3c000000,0xbc00,
0xb9a83c00,0x39a80000,0xb9a80000,0xb9a83c00,0x39a80000,0x39a8bc00,0xb9a83c00,0x39a80000,0x39a8bc00,0xb9a80000,0x39a80000,0x39a8bc00,0xb9a80000,0xb9a83c00,0x39a8bc00,0xb9a80000,
0xbc003c00,0x0,0x0,0xbc003c00,0xbc003c00,0x0,0x0,0xbc003c00,0xbc003c00,0x0,0x0,0xbc003c00,0xbc003c00,0x0,0x0,0xbc003c00,
0xb9a83c00,0xb9a80000,0x39a80000,0xb9a83c00,0x39a80000,0xb9a83c00,0x39a8bc00,0x39a80000,0x39a8bc00,0x39a80000,0xb9a80000,0x39a8bc00,0xb9a80000,0x39a8bc00,0xb9a83c00,0xb9a80000,
0x3c00,0xbc000000,0x3c000000,0x3c00,0xbc00,0x3c000000,0xbc000000,0xbc00,0x3c00,0xbc000000,0x3c000000,0x3c00,0xbc00,0x3c000000,0xbc000000,0xbc00,
0x39a83c00,0xb9a80000,0x39a80000,0x39a83c00,0xb9a80000,0xb9a8bc00,0x39a83c00,0xb9a80000,0xb9a8bc00,0x39a80000,0xb9a80000,0xb9a8bc00,0x39a80000,0x39a83c00,0xb9a8bc00,0x39a80000,
0x35a835a8,0x35a835a8,0x0,0x0,0x35a835a8,0x35a835a8,0x0,0x0,0x35a835a8,0x35a835a8,0x0,0x0,0x35a835a8,0x35a835a8,0x0,0x0,
0x35a635a8,0x35193536,0x24ff1871,0x30e63065,0x359735a0,0x34d634f9,0x2aea28b6,0x31e03165,0x357b358b,0x348634af,0x2da22c8d,0x32cc3258,0x35503567,0x342b345a,0x2fc12eb3,0x33a6333b,
0x359f35a8,0x331233e7,0x28fd1c71,0x346b340c,0x35653589,0x3136322b,0x2ed52cb0,0x350534be,0x34f53533,0x2e4d3033,0x31753075,0x356f3541,0x345434aa,0x27c42c24,0x33493267,0x35a33590,
0x359435a8,0x2d183023,0x2b771eaa,0x35833544,0x35113562,0xa61b2736,0x31062ef7,0x35a535a4,0x341f34a5,0xb002acd2,0x33c03275,0x354a3587,0x31a33304,0xb2e8b184,0x34e83470,0x347b34f0,
0x358535a8,0xacf5a071,0x2cf52071,0x358535a8,0x34a0352c,0xb284b096,0x32843096,0x34a0352c,0x320e33cd,0xb4c7b419,0x34c73419,0x320e33cd,0x2bbd3012,0xb593b547,0x35933547,0x2bbd3012,
0x357135a7,0xb304b0a6,0x2e2b218d,0x34703528,0x341334e8,0xb52fb47b,0x33da31a3,0x308532e8,0x2ef731fe,0xb5a4b594,0x356234cc,0xa7362b77,0xac01261b,0xb4c3b55c,0x359135a5,0xb21daf3b,
0x355935a7,0xb515b425,0x2f5c22aa,0x30f633b3,0x32da3496,0xb59bb596,0x348032a1,0xaa172b30,0x258d2fe2,0xb43db525,0x35a5354d,0xb37fb0b6,0xb1b2ad3a,0xadc4b1ef,0x34e33581,0xb578b4d1,
0x353d35a7,0xb5a8b550,0x304423c6,0x18712fc1,0x31653437,0xb465b556,0x34f9338c,0xb320af7e,0xac472aea,0xac8db1e0,0x358e3597,0xb58bb4d6,0xb45ab1c2,0x31462a5e,0x333b34df,0xb501b59a,
0x34003400,0x34003400,0x0,0x0,0x34003400,0x34003400,0x0,0x0,0x34003400,0x34003400,0x0,0x0,0x34003400,0x34003400,0x0,0x0,
0x0,0x0,0x34003400,0x34003400,0x0,0x0,0x34003400,0x34003400,0x0,0x0,0x34003400,0x34003400,0x0,0x0,0x34003400,0x34003400,
0x333b33fe,0xb33bb3fe,0xaed7a248,0x2ed72248,0x2d64315f,0xad64b15f,0xb388b1ed,0x338831ed,0xaed7a248,0x2ed72248,0xb33bb3fe,0x333b33fe,0xb388b1ed,0x338831ed,0xad64b15f,0x2d64315f,
0x2ed72248,0xaed7a248,0x333b33fe,0xb33bb3fe,0x338831ed,0xb388b1ed,0x2d64315f,0xad64b15f,0x333b33fe,0xb33bb3fe,0xaed7a248,0x2ed72248,0x2d64315f,0xad64b15f,0xb388b1ed,0x338831ed,
0x311333f6,0x311333f6,0xb22fa646,0xb22fa646,0xb22fa646,0xb22fa646,0xb113b3f6,0xb113b3f6,0xb113b3f6,0xb113b3f6,0x322f2646,0x322f2646,0x322f2646,0x322f2646,0x311333f6,0x311333f6,
0x322f2646,0x322f2646,0x311333f6,0x311333f6,0x311333f6,0x311333f6,0xb22fa646,0xb22fa646,0xb22fa646,0xb22fa646,0xb113b3f6,0xb113b3f6,0xb113b3f6,0xb113b3f6,0x322f2646,0x322f2646,
0x2bc633ea,0xabc6b3ea,0xb3c3a8b2,0x33c328b2,0xb2ddb26d,0x32dd326d,0x301db0c4,0xb01d30c4,0x33c328b2,0xb3c3a8b2,0x2bc633ea,0xabc6b3ea,0xb01d30c4,0x301db0c4,0xb2ddb26d,0x32dd326d,
0x33c328b2,0xb3c3a8b2,0x2bc633ea,0xabc6b3ea,0xb01d30c4,0x301db0c4,0xb2ddb26d,0x32dd326d,0xabc6b3ea,0x2bc633ea,0x33c328b2,0xb3c3a8b2,0x32dd326d,0xb2ddb26d,0xb01d30c4,0x301db0c4,
0xaa3e33d9,0xaa3e33d9,0xb3d9aa3e,0xb3d9aa3e,0x2a3eb3d9,0x2a3eb3d9,0x33d92a3e,0x33d92a3e,0xaa3e33d9,0xaa3e33d9,0xb3d9aa3e,0xb3d9aa3e,0x2a3eb3d9,0x2a3eb3d9,0x33d92a3e,0x33d92a3e,
0x33d92a3e,0x33d92a3e,0xaa3e33d9,0xaa3e33d9,0xb3d9aa3e,0xb3d9aa3e,0x2a3eb3d9,0x2a3eb3d9,0x33d92a3e,0x33d92a3e,0xaa3e33d9,0xaa3e33d9,0xb3d9aa3e,0xb3d9aa3e,0x2a3eb3d9,0x2a3eb3d9,
0xb0c433c3,0x30c4b3c3,0xb26dabc6,0x326d2bc6,0x33eab01d,0xb3ea301d,0x28b232dd,0xa8b2b2dd,0xb26dabc6,0x326d2bc6,0x30c4b3c3,0xb0c433c3,0x28b232dd,0xa8b2b2dd,0xb3ea301d,0x33eab01d,
0x326d2bc6,0xb26dabc6,0xb0c433c3,0x30c4b3c3,0xa8b2b2dd,0x28b232dd,0x33eab01d,0xb3ea301d,0xb0c433c3,0x30c4b3c3,0xb26dabc6,0x326d2bc6,0x33eab01d,0xb3ea301d,0x28b232dd,0xa8b2b2dd,
0xb30e33a8,0xb30e33a8,0xaf8baca5,0xaf8baca5,0x2f8b2ca5,0x2f8b2ca5,0xb30e33a8,0xb30e33a8,0x330eb3a8,0x330eb3a8,0x2f8b2ca5,0x2f8b2ca5,0xaf8baca5,0xaf8baca5,0x330eb3a8,0x330eb3a8,
0x2f8b2ca5,0x2f8b2ca5,0xb30e33a8,0xb30e33a8,0x330eb3a8,0x330eb3a8,0x2f8b2ca5,0x2f8b2ca5,0xaf8baca5,0xaf8baca5,0x330eb3a8,0x330eb3a8,0xb30e33a8,0xb30e33a8,0xaf8baca5,0xaf8baca5,
0xb3fe3388,0x33feb388,0xa248ad64,0x22482d64,0xb15f333b,0x315fb33b,0xb1ed2ed7,0x31edaed7,0x22482d64,0xa248ad64,0xb3fe3388,0x33feb388,0x31edaed7,0xb1ed2ed7,0xb15f333b,0x315fb33b,
0x22482d64,0xa248ad64,0xb3fe3388,0x33feb388,0x31edaed7,0xb1ed2ed7,0xb15f333b,0x315fb33b,0x33feb388,0xb3fe3388,0x22482d64,0xa248ad64,0x315fb33b,0xb15f333b,0x31edaed7,0xb1ed2ed7,
0xb3643364,0xb3643364,0x2e1fae1f,0x2e1fae1f,0xb3643364,0xb3643364,0x2e1fae1f,0x2e1fae1f,0xb3643364,0xb3643364,0x2e1fae1f,0x2e1fae1f,0xb3643364,0xb3643364,0x2e1fae1f,0x2e1fae1f,
0xae1f2e1f,0xae1f2e1f,0xb3643364,0xb3643364,0xae1f2e1f,0xae1f2e1f,0xb3643364,0xb3643364,0xae1f2e1f,0xae1f2e1f,0xb3643364,0xb3643364,0xae1f2e1f,0xae1f2e1f,0xb3643364,0xb3643364,
0xb15f333b,0x315fb33b,0x31edaed7,0xb1ed2ed7,0x22482d64,0xa248ad64,0x33feb388,0xb3fe3388,0x31edaed7,0xb1ed2ed7,0x315fb33b,0xb15f333b,0x33feb388,0xb3fe3388,0xa248ad64,0x22482d64,
0xb1ed2ed7,0x31edaed7,0xb15f333b,0x315fb33b,0xb3fe3388,0x33feb388,0x22482d64,0xa248ad64,0xb15f333b,0x315fb33b,0x31edaed7,0xb1ed2ed7,0x22482d64,0xa248ad64,0x33feb388,0xb3fe3388,
0xaca5330e,0xaca5330e,0x33a8af8b,0x33a8af8b,0x33a8af8b,0x33a8af8b,0x2ca5b30e,0x2ca5b30e,0x2ca5b30e,0x2ca5b30e,0xb3a82f8b,0xb3a82f8b,0xb3a82f8b,0xb3a82f8b,0xaca5330e,0xaca5330e,
0xb3a82f8b,0xb3a82f8b,0xaca5330e,0xaca5330e,0xaca5330e,0xaca5330e,0x33a8af8b,0x33a8af8b,0x33a8af8b,0x33a8af8b,0x2ca5b30e,0x2ca5b30e,0x2ca5b30e,0x2ca5b30e,0xb3a82f8b,0xb3a82f8b,
0x28b232dd,0xa8b2b2dd,0x33eab01d,0xb3ea301d,0x30c4b3c3,0xb0c433c3,0xb26dabc6,0x326d2bc6,0xb3ea301d,0x33eab01d,0x28b232dd,0xa8b2b2dd,0x326d2bc6,0xb26dabc6,0x30c4b3c3,0xb0c433c3,
0xb3ea301d,0x33eab01d,0x28b232dd,0xa8b2b2dd,0x326d2bc6,0xb26dabc6,0x30c4b3c3,0xb0c433c3,0xa8b2b2dd,0x28b232dd,0xb3ea301d,0x33eab01d,0xb0c433c3,0x30c4b3c3,0x326d2bc6,0xb26dabc6,
0x307232a7,0x307232a7,0x32a7b072,0x32a7b072,0xb072b2a7,0xb072b2a7,0xb2a73072,0xb2a73072,0x307232a7,0x307232a7,0x32a7b072,0x32a7b072,0xb072b2a7,0xb072b2a7,0xb2a73072,0xb2a73072,
0xb2a73072,0xb2a73072,0x307232a7,0x307232a7,0x32a7b072,0x32a7b072,0xb072b2a7,0xb072b2a7,0xb2a73072,0xb2a73072,0x307232a7,0x307232a7,0x32a7b072,0x32a7b072,0xb072b2a7,0xb072b2a7,
0x32dd326d,0xb2ddb26d,0x301db0c4,0xb01d30c4,0xb3c3a8b2,0x33c328b2,0x2bc633ea,0xabc6b3ea,0x301db0c4,0xb01d30c4,0xb2ddb26d,0x32dd326d,0x2bc633ea,0xabc6b3ea,0x33c328b2,0xb3c3a8b2,
0xb01d30c4,0x301db0c4,0x32dd326d,0xb2ddb26d,0xabc6b3ea,0x2bc633ea,0xb3c3a8b2,0x33c328b2,0x32dd326d,0xb2ddb26d,0x301db0c4,0xb01d30c4,0xb3c3a8b2,0x33c328b2,0x2bc633ea,0xabc6b3ea,
0x33f6322f,0x33f6322f,0x2646b113,0x2646b113,0xa6463113,0xa6463113,0x33f6322f,0x33f6322f,0xb3f6b22f,0xb3f6b22f,0xa6463113,0xa6463113,0x2646b113,0x2646b113,0xb3f6b22f,0xb3f6b22f,
0xa6463113,0xa6463113,0x33f6322f,0x33f6322f,0xb3f6b22f,0xb3f6b22f,0xa6463113,0xa6463113,0x2646b113,0x2646b113,0xb3f6b22f,0xb3f6b22f,0x33f6322f,0x33f6322f,0x2646b113,0x2646b113,
0x338831ed,0xb388b1ed,0xad64b15f,0x2d64315f,0x333b33fe,0xb33bb3fe,0x2ed72248,0xaed7a248,0x2d64315f,0xad64b15f,0x338831ed,0xb388b1ed,0xaed7a248,0x2ed72248,0x333b33fe,0xb33bb3fe,
0x2d64315f,0xad64b15f,0x338831ed,0xb388b1ed,0xaed7a248,0x2ed72248,0x333b33fe,0xb33bb3fe,0xb388b1ed,0x338831ed,0x2d64315f,0xad64b15f,0xb33bb3fe,0x333b33fe,0xaed7a248,0x2ed72248,
0x3400,0x3400,0x2ca533a8,0x2ca533a8,0x24b533fa,0xa4b5b3fa,0x2dc23377,0xadc2b377,0x28b233ea,0x28b233ea,0x2ed7333b,0x2ed7333b,0x2b0333ce,0xab03b3ce,0x2fe332f6,0xafe3b2f6,
0x3400,0x3400,0x33a8aca5,0x33a8aca5,0x2f323325,0xaf32b325,0x31cbb184,0xb1cb3184,0x326d30c4,0x326d30c4,0x2d64b388,0x2d64b388,0x33e22979,0xb3e2a979,0xa7d6b3f1,0x27d633f1,
0x3400,0x3400,0xaca5b3a8,0xaca5b3a8,0x320f313a,0xb20fb13a,0xb350ae7c,0x33502e7c,0x33eaa8b2,0x33eaa8b2,0xb33b2ed7,0xb33b2ed7,0x3048b2c2,0xb04832c2,0xac4433b6,0x2c44b3b6,
0x3400,0x3400,0xb3a82ca5,0xb3a82ca5,0x33992d05,0xb399ad05,0x9e4833ff,0x1e48b3ff,0x30c4b26d,0x30c4b26d,0x33882d64,0x33882d64,0xb09bb28a,0x309b328a,0x30ecb24f,0xb0ec324f,
0x3400,0x3400,0x2ca533a8,0x2ca533a8,0x33faa4b5,0xb3fa24b5,0x3377adc2,0xb3772dc2,0xa8b2b3ea,0xa8b2b3ea,0xaed7b33b,0xaed7b33b,0xb3ce2b03,0x33ceab03,0xb2f62fe3,0x32f6afe3,
0x3400,0x3400,0x33a8aca5,0x33a8aca5,0x3325af32,0xb3252f32,0xb184b1cb,0x318431cb,0xb26db0c4,0xb26db0c4,0xad643388,0xad643388,0xa97933e2,0x2979b3e2,0x33f1a7d6,0xb3f127d6,
0x3400,0x3400,0xaca5b3a8,0xaca5b3a8,0x313ab20f,0xb13a320f,0xae7c3350,0x2e7cb350,0xb3ea28b2,0xb3ea28b2,0x333baed7,0x333baed7,0x32c23048,0xb2c2b048,0xb3b6ac44,0x33b62c44,
0x3400,0x3400,0xb3a82ca5,0xb3a82ca5,0x2d05b399,0xad053399,0x33ff1e48,0xb3ff9e48,0xb0c4326d,0xb0c4326d,0xb388ad64,0xb388ad64,0x328ab09b,0xb28a309b,0x324f30ec,0xb24fb0ec,
0x307232a7,0x307232a7,0x322f3113,0x322f3113,0x30ec324f,0xb0ecb24f,0x328a309b,0xb28ab09b,0x315f31ed,0x315f31ed,0x32dd301d,0x32dd301d,0x31cb3184,0xb1cbb184,0x33252f32,0xb325af32,
0xb072b2a7,0xb072b2a7,0xb113322f,0xb113322f,0xb2f6afe3,0x32f62fe3,0xab0333ce,0x2b03b3ce,0xb3fea248,0xb3fea248,0x2bc633c3,0x2bc633c3,0xb3502e7c,0x3350ae7c,0x313a320f,0xb13ab20f,
0x307232a7,0x307232a7,0xb22fb113,0xb22fb113,0x33f127d6,0xb3f1a7d6,0xb3e22979,0x33e2a979,0x31edb15f,0x31edb15f,0xb01d32dd,0xb01d32dd,0x9e48b3ff,0x1e4833ff,0x2d053399,0xad05b399,
0xb072b2a7,0xb072b2a7,0x3113b22f,0x3113b22f,0xb3b62c44,0x33b6ac44,0xb048b2c2,0x304832c2,0xa24833fe,0xa24833fe,0xb3c32bc6,0xb3c32bc6,0x33772dc2,0xb377adc2,0xa4b533fa,0x24b5b3fa,
0x307232a7,0x307232a7,0x322f3113,0x322f3113,0x324fb0ec,0xb24f30ec,0x309bb28a,0xb09b328a,0xb15fb1ed,0xb15fb1ed,0xb2ddb01d,0xb2ddb01d,0xb18431cb,0x3184b1cb,0xaf323325,0x2f32b325,
0xb072b2a7,0xb072b2a7,0xb113322f,0xb113322f,0xafe332f6,0x2fe3b2f6,0x33ce2b03,0xb3ceab03,0x33fe2248,0x33fe2248,0xabc6b3c3,0xabc6b3c3,0xae7cb350,0x2e7c3350,0xb20f313a,0x320fb13a,
0x307232a7,0x307232a7,0xb22fb113,0xb22fb113,0x27d6b3f1,0xa7d633f1,0x297933e2,0xa979b3e2,0xb1ed315f,0xb1ed315f,0x301db2dd,0x301db2dd,0x33ff9e48,0xb3ff1e48,0xb3992d05,0x3399ad05,
0xb072b2a7,0xb072b2a7,0x3113b22f,0x3113b22f,0x2c4433b6,0xac44b3b6,0xb2c23048,0x32c2b048,0x2248b3fe,0x2248b3fe,0x33c3abc6,0x33c3abc6,0xadc23377,0x2dc2b377,0xb3faa4b5,0x33fa24b5,
0x34000000,0x34000000,0x33a8aca5,0x33a8aca5,0x33faa4b5,0xb3fa24b5,0x3377adc2,0xb3772dc2,0x33eaa8b2,0x33eaa8b2,0x333baed7,0x333baed7,0x33ceab03,0xb3ce2b03,0x32f6afe3,0xb2f62fe3,
0x34000000,0x34000000,0xaca5b3a8,0xaca5b3a8,0x3325af32,0xb3252f32,0xb184b1cb,0x318431cb,0x30c4b26d,0x30c4b26d,0xb388ad64,0xb388ad64,0x2979b3e2,0xa97933e2,0xb3f127d6,0x33f1a7d6,
0x34000000,0x34000000,0xb3a82ca5,0xb3a82ca5,0x313ab20f,0xb13a320f,0xae7c3350,0x2e7cb350,0xa8b2b3ea,0xa8b2b3ea,0x2ed7333b,0x2ed7333b,0xb2c2b048,0x32c23048,0x33b62c44,0xb3b6ac44,
0x34000000,0x34000000,0x2ca533a8,0x2ca533a8,0x2d05b399,0xad053399,0x33ff1e48,0xb3ff9e48,0xb26db0c4,0xb26db0c4,0x2d64b388,0x2d64b388,0xb28a309b,0x328ab09b,0xb24fb0ec,0x324f30ec,
0x34000000,0x34000000,0x33a8aca5,0x33a8aca5,0xa4b5b3fa,0x24b533fa,0xadc2b377,0x2dc23377,0xb3ea28b2,0xb3ea28b2,0xb33b2ed7,0xb33b2ed7,0x2b0333ce,0xab03b3ce,0x2fe332f6,0xafe3b2f6,
0x34000000,0x34000000,0xaca5b3a8,0xaca5b3a8,0xaf32b325,0x2f323325,0xb1cb3184,0x31cbb184,0xb0c4326d,0xb0c4326d,0x33882d64,0x33882d64,0x33e22979,0xb3e2a979,0xa7d6b3f1,0x27d633f1,
0x34000000,0x34000000,0xb3a82ca5,0xb3a82ca5,0xb20fb13a,0x320f313a,0x33502e7c,0xb350ae7c,0x28b233ea,0x28b233ea,0xaed7b33b,0xaed7b33b,0x3048b2c2,0xb04832c2,0xac4433b6,0x2c44b3b6,
0x34000000,0x34000000,0x2ca533a8,0x2ca533a8,0xb399ad05,0x33992d05,0x1e48b3ff,0x9e4833ff,0x326d30c4,0x326d30c4,0xad643388,0xad643388,0xb09bb28a,0x309b328a,0x30ecb24f,0xb0ec324f,
0x32a7b072,0x32a7b072,0x3113b22f,0x3113b22f,0x324fb0ec,0xb24f30ec,0x309bb28a,0xb09b328a,0x31edb15f,0x31edb15f,0x301db2dd,0x301db2dd,0x3184b1cb,0xb18431cb,0x2f32b325,0xaf323325,
0xb2a73072,0xb2a73072,0x322f3113,0x322f3113,0xafe332f6,0x2fe3b2f6,0x33ce2b03,0xb3ceab03,0xa24833fe,0xa24833fe,0x33c3abc6,0x33c3abc6,0x2e7c3350,0xae7cb350,0x320fb13a,0xb20f313a,
0x32a7b072,0x32a7b072,0xb113322f,0xb113322f,0x27d6b3f1,0xa7d633f1,0x297933e2,0xa979b3e2,0xb15fb1ed,0xb15fb1ed,0x32dd301d,0x32dd301d,0xb3ff1e48,0x33ff9e48,0x3399ad05,0xb3992d05,
0xb2a73072,0xb2a73072,0xb22fb113,0xb22fb113,0x2c4433b6,0xac44b3b6,0xb2c23048,0x32c2b048,0x33fe2248,0x33fe2248,0x2bc633c3,0x2bc633c3,0x2dc2b377,0xadc23377,0x33fa24b5,0xb3faa4b5,
0x32a7b072,0x32a7b072,0x3113b22f,0x3113b22f,0xb0ecb24f,0x30ec324f,0xb28ab09b,0x328a309b,0xb1ed315f,0xb1ed315f,0xb01d32dd,0xb01d32dd,0x31cb3184,0xb1cbb184,0x33252f32,0xb325af32,
0xb2a73072,0xb2a73072,0x322f3113,0x322f3113,0x32f62fe3,0xb2f6afe3,0x2b03b3ce,0xab0333ce,0x2248b3fe,0x2248b3fe,0xb3c32bc6,0xb3c32bc6,0xb3502e7c,0x3350ae7c,0x313a320f,0xb13ab20f,
0x32a7b072,0x32a7b072,0xb113322f,0xb113322f,0xb3f1a7d6,0x33f127d6,0x33e2a979,0xb3e22979,0x315f31ed,0x315f31ed,0xb2ddb01d,0xb2ddb01d,0x9e48b3ff,0x1e4833ff,0x2d053399,0xad05b399,
0xb2a73072,0xb2a73072,0xb22fb113,0xb22fb113,0x33b6ac44,0xb3b62c44,0x304832c2,0xb048b2c2,0xb3fea248,0xb3fea248,0xabc6b3c3,0xabc6b3c3,0x33772dc2,0xb377adc2,0xa4b533fa,0x24b5b3fa,
0x35a835a8,0x353535a8,0x1aaa0000,0x306d0000,0x35a835a8,0x300a33da,0x20ff1eaa,0x35493413,0x35a735a7,0xb0cea2aa,0x242a22aa,0x351f35a7,0x35a535a6,0xb55bb437,0x25d424ff,0x2f4c338c,
0x35a635a8,0x351735a8,0x25460000,0x30ee0000,0x3592359e,0x2ce43304,0x2be02944,0x35863470,0x356b3581,0xb327ad3a,0x2e802d3a,0x34623581,0x35313550,0xb5a8b521,0x307d2fc1,0x9d8e30c6,
0x35a035a8,0x34f735a8,0x28da0000,0x316d0000,0x355e3587,0x2662321d,0x2f2a2cd2,0x35a534c3,0x34dc3525,0xb489b0b6,0x31c930b6,0x32c43525,0x34223486,0xb54cb59a,0x33ba32cc,0xaff32a5e,
0x359635a8,0x34d335a8,0x2b0d0000,0x31e80000,0x350c3562,0xa6ef3126,0x311e2ef7,0x35a4350a,0x34033496,0xb538b2a1,0x33fa32a1,0x305d3496,0x312e32af,0xb451b597,0x35073490,0xb350aaea,
0x358a35a8,0x34ad35a8,0x2c9e0000,0x325f0000,0x349d352f,0xad073023,0x328b3085,0x35843544,0x31d933b3,0xb598b425,0x34d83425,0x2ac733b3,0x29f42f7e,0xb1abb519,0x359c3556,0xb4e5b0e6,
0x357935a8,0x348335a8,0x2db30000,0x32d30000,0x341634f0,0xb01b2e2b,0x33d43184,0x35463571,0x2ea331ef,0xb5a2b4d1,0x356934d1,0xa84c31ef,0xacc123c6,0xac13b42b,0x358835a7,0xb590b3a6,
0x356635a8,0x345735a8,0x2ec40000,0x33420000,0x32ef34a5,0xb19b2c01,0x34783275,0x34ea3591,0x24b82fe2,0xb555b54d,0x35a6354d,0xaf8f2fe2,0xb1f7ada2,0x2b53b1c2,0x34cf357b,0xb595b4df,
0x354f35a8,0x342835a8,0x2fd20000,0x33ad0000,0x318c344e,0xb2fd2736,0x34ee3356,0x347335a4,0xac592b30,0xb4b7b596,0x358d3596,0xb2422b30,0xb46db1e0,0x317cad5d,0x330b34d6,0xb4f3b57f,
0x3c003c00,0x0,0x0,0x3c003c00,0x3c003c00,0x0,0x0,0x3c003c00,0x3c003c00,0x0,0x0,0x3c003c00,0x3c003c00,0x0,0x0,0x3c003c00,
0x39a83c00,0x39a80000,0xb9a80000,0x39a83c00,0xb9a80000,0x39a83c00,0xb9a8bc00,0xb9a80000,0xb9a8bc00,0xb9a80000,0x39a80000,0xb9a8bc00,0x39a80000,0xb9a8bc00,0x39a83c00,0x39a80000,
0x3c00,0x3c000000,0xbc000000,0x3c00,0xbc00,0xbc000000,0x3c000000,0xbc00,0x3c00,0x3c000000,0xbc000000,0x3c00,0xbc00,0xbc000000,0x3c000000,0xbc00,
0xb9a83c00,0x39a80000,0xb9a80000,0xb9a83c00,0x39a80000,0x39a8bc00,0xb9a83c00,0x39a80000,0x39a8bc00,0xb9a80000,0x39a80000,0x39a8bc00,0xb9a80000,0xb9a83c00,0x39a8bc00,0xb9a80000,
0xbc003c00,0x0,0x0,0xbc003c00,0xbc003c00,0x0,0x0,0xbc003c00,0xbc003c00,0x0,0x0,0xbc003c00,0xbc003c00,0x0,0x0,0xbc003c00,
0xb9a83c00,0xb9a80000,0x39a80000,0xb9a83c00,0x39a80000,0xb9a83c00,0x39a8bc00,0x39a80000,0x39a8bc00,0x39a80000,0xb9a80000,0x39a8bc00,0xb9a80000,0x39a8bc00,0xb9a83c00,0xb9a80000,
0x3c00,0xbc000000,0x3c000000,0x3c00,0xbc00,0x3c000000,0xbc000000,0xbc00,0x3c00,0xbc000000,0x3c000000,0x3c00,0xbc00,0x3c000000,0xbc000000,0xbc00,
0x39a83c00,0xb9a80000,0x39a80000,0x39a83c00,0xb9a80000,0xb9a8bc00,0x39a83c00,0xb9a80000,0xb9a8bc00,0x39a80000,0xb9a80000,0xb9a8bc00,0x39a80000,0x39a83c00,0xb9a8bc00,0x39a80000,
0x3c003c00,0x0,0x0,0x3c003c00,0x3c003c00,0x0,0x0,0x3c003c00,0x3c003c00,0x0,0x0,0x3c003c00,0x3c003c00,0x0,0x0,0x3c003c00,
0x39a83c00,0x39a80000,0xb9a80000,0x39a83c00,0xb9a80000,0x39a83c00,0xb9a8bc00,0xb9a80000,0xb9a8bc00,0xb9a80000,0x39a80000,0xb9a8bc00,0x39a80000,0xb9a8bc00,0x39a83c00,0x39a80000,
0x3c00,0x3c000000,0xbc000000,0x3c00,0xbc00,0xbc000000,0x3c000000,0xbc00,0x3c00,0x3c000000,0xbc000000,0x3c00,0xbc00,0xbc000000,0x3c000000,0xbc00,
0xb9a83c00,0x39a80000,0xb9a80000,0xb9a83c00,0x39a80000,0x39a8bc00,0xb9a83c00,0x39a80000,0x39a8bc00,0xb9a80000,0x39a80000,0x39a8bc00,0xb9a80000,0xb9a83c00,0x39a8bc00,0xb9a80000,
0xbc003c00,0x0,0x0,0xbc003c00,0xbc003c00,0x0,0x0,0xbc003c00,0xbc003c00,0x0,0x0,0xbc003c00,0xbc003c00,0x0,0x0,0xbc003c00,
0xb9a83c00,0xb9a80000,0x39a80000,0xb9a83c00,0x39a80000,0xb9a83c00,0x39a8bc00,0x39a80000,0x39a8bc00,0x39a80000,0xb9a80000,0x39a8bc00,0xb9a80000,0x39a8bc00,0xb9a83c00,0xb9a80000,
0x3c00,0xbc000000,0x3c000000,0x3c00,0xbc00,0x3c000000,0xbc000000,0xbc00,0x3c00,0xbc000000,0x3c000000,0x3c00,0xbc00,0x3c000000,0xbc000000,0xbc00,
0x39a83c00,0xb9a80000,0x39a80000,0x39a83c00,0xb9a80000,0xb9a8bc00,0x39a83c00,0xb9a80000,0xb9a8bc00,0x39a80000,0xb9a80000,0xb9a8bc00,0x39a80000,0x39a83c00,0xb9a8bc00,0x39a80000,
0x35a835a8,0x35a835a8,0x0,0x0,0x35a835a8,0x35a835a8,0x0,0x0,0x35a835a8,0x35a835a8,0x0,0x0,0x35a835a8,0x35a835a8,0x0,0x0,
0x35a635a8,0x35173535,0x25461aaa,0x30ee306d,0x359635a0,0x34d334f7,0x2b0d28da,0x31e8316d,0x3579358a,0x348334ad,0x2db32c9e,0x32d3325f,0x354f3566,0x34283457,0x2fd22ec4,0x33ad3342,
0x359e35a8,0x330433da,0x29441eaa,0x34703413,0x35623587,0x3126321d,0x2ef72cd2,0x350a34c3,0x34f0352f,0x2e2b3023,0x31843085,0x35713544,0x344e34a5,0x27362c01,0x33563275,0x35a43591,
0x359235a8,0x2ce4300a,0x2be020ff,0x35863549,0x350c355e,0xa6ef2662,0x311e2f2a,0x35a435a5,0x3416349d,0xb01bad07,0x33d4328b,0x35463584,0x318c32ef,0xb2fdb19b,0x34ee3478,0x347334ea,
0x358135a7,0xad3aa2aa,0x2d3a22aa,0x358135a7,0x34963525,0xb2a1b0b6,0x32a130b6,0x34963525,0x31ef33b3,0xb4d1b425,0x34d13425,0x31ef33b3,0x2b302fe2,0xb596b54d,0x3596354d,0x2b302fe2,
0x356b35a7,0xb327b0ce,0x2e80242a,0x3462351f,0x340334dc,0xb538b489,0x33fa31c9,0x305d32c4,0x2ea331d9,0xb5a2b598,0x356934d8,0xa84c2ac7,0xac5924b8,0xb4b7b555,0x358d35a6,0xb242af8f,
0x355035a6,0xb521b437,0x2fc124ff,0x30c6338c,0x32af3486,0xb597b59a,0x349032cc,0xaaea2a5e,0x23c62f7e,0xb42bb519,0x35a73556,0xb3a6b0e6,0xb1e0ada2,0xad5db1c2,0x34d6357b,0xb57fb4df,
0x353135a5,0xb5a8b55b,0x307d25d4,0x9d8e2f4c,0x312e3422,0xb451b54c,0x350733ba,0xb350aff3,0xacc129f4,0xac13b1ab,0x3588359c,0xb590b4e5,0xb46db1f7,0x317c2b53,0x330b34cf,0xb4f3b595,
0x34003400,0x34003400,0x0,0x0,0x34003400,0x34003400,0x0,0x0,0x34003400,0x34003400,0x0,0x0,0x34003400,0x34003400,0x0,0x0,
0x0,0x0,0x34003400,0x34003400,0x0,0x0,0x34003400,0x34003400,0x0,0x0,0x34003400,0x34003400,0x0,0x0,0x34003400,0x34003400,
0x332533fa,0xb325b3fa,0xaf32a4b5,0x2f3224b5,0x2d05313a,0xad05b13a,0xb399b20f,0x3399320f,0xaf32a4b5,0x2f3224b5,0xb325b3fa,0x332533fa,0xb399b20f,0x3399320f,0xad05b13a,0x2d05313a,
0x2f3224b5,0xaf32a4b5,0x332533fa,0xb325b3fa,0x3399320f,0xb399b20f,0x2d05313a,0xad05b13a,0x332533fa,0xb325b3fa,0xaf32a4b5,0x2f3224b5,0x2d05313a,0xad05b13a,0xb399b20f,0x3399320f,
0x30c433ea,0x30c433ea,0xb26da8b2,0xb26da8b2,0xb26da8b2,0xb26da8b2,0xb0c4b3ea,0xb0c4b3ea,0xb0c4b3ea,0xb0c4b3ea,0x326d28b2,0x326d28b2,0x326d28b2,0x326d28b2,0x30c433ea,0x30c433ea,
0x326d28b2,0x326d28b2,0x30c433ea,0x30c433ea,0x30c433ea,0x30c433ea,0xb26da8b2,0xb26da8b2,0xb26da8b2,0xb26da8b2,0xb0c4b3ea,0xb0c4b3ea,0xb0c4b3ea,0xb0c4b3ea,0x326d28b2,0x326d28b2,
0x297933ce,0xa979b3ce,0xb3e2ab03,0x33e22b03,0xb28ab2c2,0x328a32c2,0x309bb048,0xb09b3048,0x33e22b03,0xb3e2ab03,0x297933ce,0xa979b3ce,0xb09b3048,0x309bb048,0xb28ab2c2,0x328a32c2,
0x33e22b03,0xb3e2ab03,0x297933ce,0xa979b3ce,0xb09b3048,0x309bb048,0xb28ab2c2,0x328a32c2,0xa979b3ce,0x297933ce,0x33e22b03,0xb3e2ab03,0x328a32c2,0xb28ab2c2,0xb09b3048,0x309bb048,
0xaca533a8,0xaca533a8,0xb3a8aca5,0xb3a8aca5,0x2ca5b3a8,0x2ca5b3a8,0x33a82ca5,0x33a82ca5,0xaca533a8,0xaca533a8,0xb3a8aca5,0xb3a8aca5,0x2ca5b3a8,0x2ca5b3a8,0x33a82ca5,0x33a82ca5,
0x33a82ca5,0x33a82ca5,0xaca533a8,0xaca533a8,0xb3a8aca5,0xb3a8aca5,0x2ca5b3a8,0x2ca5b3a8,0x33a82ca5,0x33a82ca5,0xaca533a8,0xaca533a8,0xb3a8aca5,0xb3a8aca5,0x2ca5b3a8,0x2ca5b3a8,
0xb1843377,0x3184b377,0xb1cbadc2,0x31cb2dc2,0x33ffae7c,0xb3ff2e7c,0x1e483350,0x9e48b350,0xb1cbadc2,0x31cb2dc2,0x3184b377,0xb1843377,0x1e483350,0x9e48b350,0xb3ff2e7c,0x33ffae7c,
0x31cb2dc2,0xb1cbadc2,0xb1843377,0x3184b377,0x9e48b350,0x1e483350,0x33ffae7c,0xb3ff2e7c,0xb1843377,0x3184b377,0xb1cbadc2,0x31cb2dc2,0x33ffae7c,0xb3ff2e7c,0x1e483350,0x9e48b350,
0xb388333b,0xb388333b,0xad64aed7,0xad64aed7,0x2d642ed7,0x2d642ed7,0xb388333b,0xb388333b,0x3388b33b,0x3388b33b,0x2d642ed7,0x2d642ed7,0xad64aed7,0xad64aed7,0x3388b33b,0x3388b33b,
0x2d642ed7,0x2d642ed7,0xb388333b,0xb388333b,0x3388b33b,0x3388b33b,0x2d642ed7,0x2d642ed7,0xad64aed7,0xad64aed7,0x3388b33b,0x3388b33b,0xb388333b,0xb388333b,0xad64aed7,0xad64aed7,
0xb3f132f6,0x33f1b2f6,0x27d6afe3,0xa7d62fe3,0xb24f33b6,0x324fb3b6,0xb0ec2c44,0x30ecac44,0xa7d62fe3,0x27d6afe3,0xb3f132f6,0x33f1b2f6,0x30ecac44,0xb0ec2c44,0xb24f33b6,0x324fb3b6,
0xa7d62fe3,0x27d6afe3,0xb3f132f6,0x33f1b2f6,0x30ecac44,0xb0ec2c44,0xb24f33b6,0x324fb3b6,0x33f1b2f6,0xb3f132f6,0xa7d62fe3,0x27d6afe3,0x324fb3b6,0xb24f33b6,0x30ecac44,0xb0ec2c44,
0xb2a732a7,0xb2a732a7,0x3072b072,0x3072b072,0xb2a732a7,0xb2a732a7,0x3072b072,0x3072b072,0xb2a732a7,0xb2a732a7,0x3072b072,0x3072b072,0xb2a732a7,0xb2a732a7,0x3072b072,0x3072b072,
0xb0723072,0xb0723072,0xb2a732a7,0xb2a732a7,0xb0723072,0xb0723072,0xb2a732a7,0xb2a732a7,0xb0723072,0xb0723072,0xb2a732a7,0xb2a732a7,0xb0723072,0xb0723072,0xb2a732a7,0xb2a732a7,
0xafe3324f,0x2fe3b24f,0x32f6b0ec,0xb2f630ec,0x2c4427d6,0xac44a7d6,0x33b6b3f1,0xb3b633f1,0x32f6b0ec,0xb2f630ec,0x2fe3b24f,0xafe3324f,0x33b6b3f1,0xb3b633f1,0xac44a7d6,0x2c4427d6,
0xb2f630ec,0x32f6b0ec,0xafe3324f,0x2fe3b24f,0xb3b633f1,0x33b6b3f1,0x2c4427d6,0xac44a7d6,0xafe3324f,0x2fe3b24f,0x32f6b0ec,0xb2f630ec,0x2c4427d6,0xac44a7d6,0x33b6b3f1,0xb3b633f1,
0xa24831ed,0xa24831ed,0x33feb15f,0x33feb15f,0x33feb15f,0x33feb15f,0x2248b1ed,0x2248b1ed,0x2248b1ed,0x2248b1ed,0xb3fe315f,0xb3fe315f,0xb3fe315f,0xb3fe315f,0xa24831ed,0xa24831ed,
0xb3fe315f,0xb3fe315f,0xa24831ed,0xa24831ed,0xa24831ed,0xa24831ed,0x33feb15f,0x33feb15f,0x33feb15f,0x33feb15f,0x2248b1ed,0x2248b1ed,0x2248b1ed,0x2248b1ed,0xb3fe315f,0xb3fe315f,
0x2e7c3184,0xae7cb184,0x3350b1cb,0xb35031cb,0x2dc2b3ff,0xadc233ff,0xb3771e48,0x33779e48,0xb35031cb,0x3350b1cb,0x2e7c3184,0xae7cb184,0x33779e48,0xb3771e48,0x2dc2b3ff,0xadc233ff,
0xb35031cb,0x3350b1cb,0x2e7c3184,0xae7cb184,0x33779e48,0xb3771e48,0x2dc2b3ff,0xadc233ff,0xae7cb184,0x2e7c3184,0xb35031cb,0x3350b1cb,0xadc233ff,0x2dc2b3ff,0x33779e48,0xb3771e48,
0x322f3113,0x322f3113,0x3113b22f,0x3113b22f,0xb22fb113,0xb22fb113,0xb113322f,0xb113322f,0x322f3113,0x322f3113,0x3113b22f,0x3113b22f,0xb22fb113,0xb22fb113,0xb113322f,0xb113322f,
0xb113322f,0xb113322f,0x322f3113,0x322f3113,0x3113b22f,0x3113b22f,0xb22fb113,0xb22fb113,0xb113322f,0xb113322f,0x322f3113,0x322f3113,0x3113b22f,0x3113b22f,0xb22fb113,0xb22fb113,
0x33ce309b,0xb3ceb09b,0x2b03b28a,0xab03328a,0xb2c22979,0x32c2a979,0x304833e2,0xb048b3e2,0x2b03b28a,0xab03328a,0xb3ceb09b,0x33ce309b,0x304833e2,0xb048b3e2,0x32c2a979,0xb2c22979,
0xab03328a,0x2b03b28a,0x33ce309b,0xb3ceb09b,0xb048b3e2,0x304833e2,0xb2c22979,0x32c2a979,0x33ce309b,0xb3ceb09b,0x2b03b28a,0xab03328a,0xb2c22979,0x32c2a979,0x304833e2,0xb048b3e2,
0x33c3301d,0x33c3301d,0xabc6b2dd,0xabc6b2dd,0x2bc632dd,0x2bc632dd,0x33c3301d,0x33c3301d,0xb3c3b01d,0xb3c3b01d,0x2bc632dd,0x2bc632dd,0xabc6b2dd,0xabc6b2dd,0xb3c3b01d,0xb3c3b01d,
0x2bc632dd,0x2bc632dd,0x33c3301d,0x33c3301d,0xb3c3b01d,0xb3c3b01d,0x2bc632dd,0x2bc632dd,0xabc6b2dd,0xabc6b2dd,0xb3c3b01d,0xb3c3b01d,0x33c3301d,0x33c3301d,0xabc6b2dd,0xabc6b2dd,
0x320f2f32,0xb20faf32,0xb13ab325,0x313a3325,0x33fa3399,0xb3fab399,0x24b5ad05,0xa4b52d05,0x313a3325,0xb13ab325,0x320f2f32,0xb20faf32,0xa4b52d05,0x24b5ad05,0x33fa3399,0xb3fab399,
0x313a3325,0xb13ab325,0x320f2f32,0xb20faf32,0xa4b52d05,0x24b5ad05,0x33fa3399,0xb3fab399,0xb20faf32,0x320f2f32,0x313a3325,0xb13ab325,0xb3fab399,0x33fa3399,0xa4b52d05,0x24b5ad05,
0x3400,0x3400,0x2e1f3364,0x2e1f3364,0x264633f6,0xa646b3f6,0x2f8b330e,0xaf8bb30e,0x2a3e33d9,0x2a3e33d9,0x307232a7,0x307232a7,0x2ca533a8,0xaca5b3a8,0x3113322f,0xb113b22f,
0x3400,0x3400,0x3364ae1f,0x3364ae1f,0x2f8b330e,0xaf8bb30e,0x3113b22f,0xb113322f,0x32a73072,0x32a73072,0x2a3eb3d9,0x2a3eb3d9,0x33f62646,0xb3f6a646,0xaca5b3a8,0x2ca533a8,
0x3400,0x3400,0xae1fb364,0xae1fb364,0x322f3113,0xb22fb113,0xb3a8aca5,0x33a82ca5,0x33d9aa3e,0x33d9aa3e,0xb2a73072,0xb2a73072,0x2f8bb30e,0xaf8b330e,0xa64633f6,0x2646b3f6,
0x3400,0x3400,0xb3642e1f,0xb3642e1f,0x33a82ca5,0xb3a8aca5,0x264633f6,0xa646b3f6,0x3072b2a7,0x3072b2a7,0x33d92a3e,0x33d92a3e,0xb113b22f,0x3113322f,0x2f8bb30e,0xaf8b330e,
0x3400,0x3400,0x2e1f3364,0x2e1f3364,0x33f6a646,0xb3f62646,0x330eaf8b,0xb30e2f8b,0xaa3eb3d9,0xaa3eb3d9,0xb072b2a7,0xb072b2a7,0xb3a82ca5,0x33a8aca5,0xb22f3113,0x322fb113,
0x3400,0x3400,0x3364ae1f,0x3364ae1f,0x330eaf8b,0xb30e2f8b,0xb22fb113,0x322f3113,0xb2a7b072,0xb2a7b072,0xaa3e33d9,0xaa3e33d9,0xa64633f6,0x2646b3f6,0x33a8aca5,0xb3a82ca5,
0x3400,0x3400,0xae1fb364,0xae1fb364,0x3113b22f,0xb113322f,0xaca533a8,0x2ca5b3a8,0xb3d92a3e,0xb3d92a3e,0x32a7b072,0x32a7b072,0x330e2f8b,0xb30eaf8b,0xb3f6a646,0x33f62646,
0x3400,0x3400,0xb3642e1f,0xb3642e1f,0x2ca5b3a8,0xaca533a8,0x33f6a646,0xb3f62646,0xb07232a7,0xb07232a7,0xb3d9aa3e,0xb3d9aa3e,0x322fb113,0xb22f3113,0x330e2f8b,0xb30eaf8b,
0x31a831a8,0x31a831a8,0x33642e1f,0x33642e1f,0x322f3113,0xb22fb113,0x33a82ca5,0xb3a8aca5,0x32a73072,0x32a73072,0x33d92a3e,0x33d92a3e,0x330e2f8b,0xb30eaf8b,0x33f62646,0xb3f6a646,
0xb1a8b1a8,0xb1a8b1a8,0xae1f3364,0xae1f3364,0xb3a8aca5,0x33a82ca5,0x264633f6,0xa646b3f6,0xb3d92a3e,0xb3d92a3e,0x307232a7,0x307232a7,0xb22f3113,0x322fb113,0x330e2f8b,0xb30eaf8b,
0x31a831a8,0x31a831a8,0xb364ae1f,0xb364ae1f,0x33f6a646,0xb3f62646,0xb30e2f8b,0x330eaf8b,0x3072b2a7,0x3072b2a7,0xaa3e33d9,0xaa3e33d9,0xaca5b3a8,0x2ca533a8,0x3113322f,0xb113b22f,
0xb1a8b1a8,0xb1a8b1a8,0x2e1fb364,0x2e1fb364,0xb30e2f8b,0x330eaf8b,0xb22fb113,0x322f3113,0x2a3e33d9,0x2a3e33d9,0xb2a73072,0xb2a73072,0x33f62646,0xb3f6a646,0x2ca533a8,0xaca5b3a8,
0x31a831a8,0x31a831a8,0x33642e1f,0x33642e1f,0x3113b22f,0xb113322f,0x2ca5b3a8,0xaca533a8,0xb2a7b072,0xb2a7b072,0xb3d9aa3e,0xb3d9aa3e,0xaf8b330e,0x2f8bb30e,0xa64633f6,0x2646b3f6,
0xb1a8b1a8,0xb1a8b1a8,0xae1f3364,0xae1f3364,0xaca533a8,0x2ca5b3a8,0x33f6a646,0xb3f62646,0x33d9aa3e,0x33d9aa3e,0xb072b2a7,0xb072b2a7,0xb113b22f,0x3113322f,0xaf8b330e,0x2f8bb30e,
0x31a831a8,0x31a831a8,0xb364ae1f,0xb364ae1f,0xa646b3f6,0x264633f6,0x2f8b330e,0xaf8bb30e,0xb07232a7,0xb07232a7,0x2a3eb3d9,0x2a3eb3d9,0x33a8aca5,0xb3a82ca5,0xb22f3113,0x322fb113,
0xb1a8b1a8,0xb1a8b1a8,0x2e1fb364,0x2e1fb364,0x2f8b330e,0xaf8bb30e,0xb113322f,0x3113b22f,0xaa3eb3d9,0xaa3eb3d9,0x32a7b072,0x32a7b072,0xa64633f6,0x2646b3f6,0xb3a82ca5,0x33a8aca5,
0x34000000,0x34000000,0x3364ae1f,0x3364ae1f,0x33f6a646,0xb3f62646,0x330eaf8b,0xb30e2f8b,0x33d9aa3e,0x33d9aa3e,0x32a7b072,0x32a7b072,0x33a8aca5,0xb3a82ca5,0x322fb113,0xb22f3113,
0x34000000,0x34000000,0xae1fb364,0xae1fb364,0x330eaf8b,0xb30e2f8b,0xb22fb113,0x322f3113,0x3072b2a7,0x3072b2a7,0xb3d9aa3e,0xb3d9aa3e,0x2646b3f6,0xa64633f6,0xb3a82ca5,0x33a8aca5,
0x34000000,0x34000000,0xb3642e1f,0xb3642e1f,0x3113b22f,0xb113322f,0xaca533a8,0x2ca5b3a8,0xaa3eb3d9,0xaa3eb3d9,0x307232a7,0x307232a7,0xb30eaf8b,0x330e2f8b,0x33f62646,0xb3f6a646,
0x34000000,0x34000000,0x2e1f3364,0x2e1f3364,0x2ca5b3a8,0xaca533a8,0x33f6a646,0xb3f62646,0xb2a7b072,0xb2a7b072,0x2a3eb3d9,0x2a3eb3d9,0xb22f3113,0x322fb113,0xb30eaf8b,0x330e2f8b,
0x34000000,0x34000000,0x3364ae1f,0x3364ae1f,0xa646b3f6,0x264633f6,0xaf8bb30e,0x2f8b330e,0xb3d92a3e,0xb3d92a3e,0xb2a73072,0xb2a73072,0x2ca533a8,0xaca5b3a8,0x3113322f,0xb113b22f,
0x34000000,0x34000000,0xae1fb364,0xae1fb364,0xaf8bb30e,0x2f8b330e,0xb113322f,0x3113b22f,0xb07232a7,0xb07232a7,0x33d92a3e,0x33d92a3e,0x33f62646,0xb3f6a646,0xaca5b3a8,0x2ca533a8,
0x34000000,0x34000000,0xb3642e1f,0xb3642e1f,0xb22fb113,0x322f3113,0x33a82ca5,0xb3a8aca5,0x2a3e33d9,0x2a3e33d9,0xb072b2a7,0xb072b2a7,0x2f8bb30e,0xaf8b330e,0xa64633f6,0x2646b3f6,
0x34000000,0x34000000,0x2e1f3364,0x2e1f3364,0xb3a8aca5,0x33a82ca5,0xa646b3f6,0x264633f6,0x32a73072,0x32a73072,0xaa3e33d9,0xaa3e33d9,0xb113b22f,0x3113322f,0x2f8bb30e,0xaf8b330e,
0x31a8b1a8,0x31a8b1a8,0x2e1fb364,0x2e1fb364,0x3113b22f,0xb113322f,0x2ca5b3a8,0xaca533a8,0x3072b2a7,0x3072b2a7,0x2a3eb3d9,0x2a3eb3d9,0x2f8bb30e,0xaf8b330e,0x2646b3f6,0xa64633f6,
0xb1a831a8,0xb1a831a8,0x33642e1f,0x33642e1f,0xaca533a8,0x2ca5b3a8,0x33f6a646,0xb3f62646,0x2a3e33d9,0x2a3e33d9,0x32a7b072,0x32a7b072,0x3113322f,0xb113b22f,0x2f8bb30e,0xaf8b330e,
0x31a8b1a8,0x31a8b1a8,0xae1f3364,0xae1f3364,0xa646b3f6,0x264633f6,0x2f8b330e,0xaf8bb30e,0xb2a7b072,0xb2a7b072,0x33d92a3e,0x33d92a3e,0xb3a82ca5,0x33a8aca5,0x322fb113,0xb22f3113,
0xb1a831a8,0xb1a831a8,0xb364ae1f,0xb364ae1f,0x2f8b330e,0xaf8bb30e,0xb113322f,0x3113b22f,0x33d9aa3e,0x33d9aa3e,0x307232a7,0x307232a7,0x2646b3f6,0xa64633f6,0x33a8aca5,0xb3a82ca5,
0x31a8b1a8,0x31a8b1a8,0x2e1fb364,0x2e1fb364,0xb22fb113,0x322f3113,0xb3a8aca5,0x33a82ca5,0xb07232a7,0xb07232a7,0xaa3e33d9,0xaa3e33d9,0x330e2f8b,0xb30eaf8b,0x33f62646,0xb3f6a646,
0xb1a831a8,0xb1a831a8,0x33642e1f,0x33642e1f,0x33a82ca5,0xb3a8aca5,0xa646b3f6,0x264633f6,0xaa3eb3d9,0xaa3eb3d9,0xb2a73072,0xb2a73072,0xb22f3113,0x322fb113,0x330e2f8b,0xb30eaf8b,
0x31a8b1a8,0x31a8b1a8,0xae1f3364,0xae1f3364,0xb3f62646,0x33f6a646,0x330eaf8b,0xb30e2f8b,0x32a73072,0x32a73072,0xb3d9aa3e,0xb3d9aa3e,0xaca5b3a8,0x2ca533a8,0x3113322f,0xb113b22f,
0xb1a831a8,0xb1a831a8,0xb364ae1f,0xb364ae1f,0x330eaf8b,0xb30e2f8b,0x322f3113,0xb22fb113,0xb3d92a3e,0xb3d92a3e,0xb072b2a7,0xb072b2a7,0x33f62646,0xb3f6a646,0x2ca533a8,0xaca5b3a8,
0x35a835a8,0x353335a8,0x1c710000,0x30750000,0x35a735a8,0x2fe233cd,0x22aa2071,0x354d3419,0x35a535a6,0xb0f6a471,0x258d2471,0x351535a6,0x35a335a4,0xb565b449,0x27c426a9,0x2ed53364,
0x35a535a8,0x351535a8,0x258d0000,0x30f60000,0x3590359d,0x2cb032f6,0x2c24298a,0x35893476,0x3565357d,0xb349ad7f,0x2ed52d7f,0x3454357d,0x35253547,0xb5a7b52c,0x30b63012,0xa2aa3096,
0x359f35a8,0x34f535a8,0x28fd0000,0x31750000,0x35593585,0x258d320e,0x2f5c2cf5,0x35a534c7,0x34d1351d,0xb496b0d6,0x31ef30d6,0x32a1351d,0x340c3476,0xb541b59d,0x33e732f6,0xb033298a,
0x359635a8,0x34d135a8,0x2b300000,0x31ef0000,0x3505355f,0xa7c43116,0x31362f19,0x35a3350e,0x33e7348b,0xb541b2bd,0x340c32bd,0x3033348b,0x30f63284,0xb43db593,0x351534a0,0xb37fabbd,
0x358935a8,0x34aa35a8,0x2cb00000,0x32670000,0x3496352c,0xad3a3012,0x32a13096,0x35813547,0x31b23399,0xb59bb431,0x34e33431,0x2a173399,0x28fd2f19,0xb175b50e,0x359f355f,0xb4f5b116,
0x357835a8,0x348035a8,0x2dc40000,0x32da0000,0x340c34ec,0xb0332e09,0x33e73194,0x35413574,0x2e4d31d1,0xb59fb4da,0x356f34da,0xa8fd31d1,0xad3a2071,0xab30b419,0x358135a8,0xb596b3cd,
0x356535a8,0x345435a8,0x2ed50000,0x33490000,0x32da34a0,0xb1b22bbd,0x34803284,0x34e33593,0x22aa2f9f,0xb54db554,0x35a73554,0xafe22f9f,0xb22bae09,0x2c24b194,0x34be3574,0xb590b4ec,
0x354d35a8,0x342535a8,0x2fe20000,0x33b30000,0x31753449,0xb31226a9,0x34f53364,0x346b35a4,0xacb02aa4,0xb4aab598,0x35893598,0xb2672aa4,0xb480b20e,0x31b2acf5,0x32da34c7,0xb4e3b585,
0x3c003c00,0x0,0x0,0x3c003c00,0x3c003c00,0x0,0x0,0x3c003c00,0x3c003c00,0x0,0x0,0x3c003c00,0x3c003c00,0x0,0x0,0x3c003c00,
0x39a83c00,0x39a80000,0xb9a80000,0x39a83c00,0xb9a80000,0x39a83c00,0xb9a8bc00,0xb9a80000,0xb9a8bc00,0xb9a80000,0x39a80000,0xb9a8bc00,0x39a80000,0xb9a8bc00,0x39a83c00,0x39a80000,
0x3c00,0x3c000000,0xbc000000,0x3c00,0xbc00,0xbc000000,0x3c000000,0xbc00,0x3c00,0x3c000000,0xbc000000,0x3c00,0xbc00,0xbc000000,0x3c000000,0xbc00,
0xb9a83c00,0x39a80000,0xb9a80000,0xb9a83c00,0x39a80000,0x39a8bc00,0xb9a83c00,0x39a80000,0x39a8bc00,0xb9a80000,0x39a80000,0x39a8bc00,0xb9a80000,0xb9a83c00,0x39a8bc00,0xb9a80000,
0xbc003c00,0x0,0x0,0xbc003c00,0xbc003c00,0x0,0x0,0xbc003c00,0xbc003c00,0x0,0x0,0xbc003c00,0xbc003c00,0x0,0x0,0xbc003c00,
0xb9a83c00,0xb9a80000,0x39a80000,0xb9a83c00,0x39a80000,0xb9a83c00,0x39a8bc00,0x39a80000,0x39a8bc00,0x39a80000,0xb9a80000,0x39a8bc00,0xb9a80000,0x39a8bc00,0xb9a83c00,0xb9a80000,
0x3c00,0xbc000000,0x3c000000,0x3c00,0xbc00,0x3c000000,0xbc000000,0xbc00,0x3c00,0xbc000000,0x3c000000,0x3c00,0xbc00,0x3c000000,0xbc000000,0xbc00,
0x39a83c00,0xb9a80000,0x39a80000,0x39a83c00,0xb9a80000,0xb9a8bc00,0x39a83c00,0xb9a80000,0xb9a8bc00,0x39a80000,0xb9a80000,0xb9a8bc00,0x39a80000,0x39a83c00,0xb9a8bc00,0x39a80000,
0x3c003c00,0x0,0x0,0x3c003c00,0x3c003c00,0x0,0x0,0x3c003c00,0x3c003c00,0x0,0x0,0x3c003c00,0x3c003c00,0x0,0x0,0x3c003c00,
0x39a83c00,0x39a80000,0xb9a80000,0x39a83c00,0xb9a80000,0x39a83c00,0xb9a8bc00,0xb9a80000,0xb9a8bc00,0xb9a80000,0x39a80000,0xb9a8bc00,0x39a80000,0xb9a8bc00,0x39a83c00,0x39a80000,
0x3c00,0x3c000000,0xbc000000,0x3c00,0xbc00,0xbc000000,0x3c000000,0xbc00,0x3c00,0x3c000000,0xbc000000,0x3c00,0xbc00,0xbc000000,0x3c000000,0xbc00,
0xb9a83c00,0x39a80000,0xb9a80000,0xb9a83c00,0x39a80000,0x39a8bc00,0xb9a83c00,0x39a80000,0x39a8bc00,0xb9a80000,0x39a80000,0x39a8bc00,0xb9a80000,0xb9a83c00,0x39a8bc00,0xb9a80000,
0xbc003c00,0x0,0x0,0xbc003c00,0xbc003c00,0x0,0x0,0xbc003c00,0xbc003c00,0x0,0x0,0xbc003c00,0xbc003c00,0x0,0x0,0xbc003c00,
0xb9a83c00,0xb9a80000,0x39a80000,0xb9a83c00,0x39a80000,0xb9a83c00,0x39a8bc00,0x39a80000,0x39a8bc00,0x39a80000,0xb9a80000,0x39a8bc00,0xb9a80000,0x39a8bc00,0xb9a83c00,0xb9a80000,
0x3c00,0xbc000000,0x3c000000,0x3c00,0xbc00,0x3c000000,0xbc000000,0xbc00,0x3c00,0xbc000000,0x3c000000,0x3c00,0xbc00,0x3c000000,0xbc000000,0xbc00,
0x39a83c00,0xb9a80000,0x39a80000,0x39a83c00,0xb9a80000,0xb9a8bc00,0x39a83c00,0xb9a80000,0xb9a8bc00,0x39a80000,0xb9a80000,0xb9a8bc00,0x39a80000,0x39a83c00,0xb9a8bc00,0x39a80000,
0x35a835a8,0x35a835a8,0x0,0x0,0x35a835a8,0x35a835a8,0x0,0x0,0x35a835a8,0x35a835a8,0x0,0x0,0x35a835a8,0x35a835a8,0x0,0x0,
0x35a535a8,0x35153533,0x258d1c71,0x30f63075,0x3596359f,0x34d134f5,0x2b3028fd,0x31ef3175,0x35783589,0x348034aa,0x2dc42cb0,0x32da3267,0x354d3565,0x34253454,0x2fe22ed5,0x33b33349,
0x359d35a8,0x32f633cd,0x298a2071,0x34763419,0x355f3585,0x3116320e,0x2f192cf5,0x350e34c7,0x34ec352c,0x2e093012,0x31943096,0x35743547,0x344934a0,0x26a92bbd,0x33643284,0x35a43593,
0x359035a7,0x2cb02fe2,0x2c2422aa,0x3589354d,0x35053559,0xa7c4258d,0x31362f5c,0x35a335a5,0x340c3496,0xb033ad3a,0x33e732a1,0x35413581,0x317532da,0xb312b1b2,0x34f53480,0x346b34e3,
0x357d35a6,0xad7fa471,0x2d7f2471,0x357d35a6,0x348b351d,0xb2bdb0d6,0x32bd30d6,0x348b351d,0x31d13399,0xb4dab431,0x34da3431,0x31d13399,0x2aa42f9f,0xb598b554,0x35983554,0x2aa42f9f,
0x356535a5,0xb349b0f6,0x2ed5258d,0x34543515,0x33e734d1,0xb541b496,0x340c31ef,0x303332a1,0x2e4d31b2,0xb59fb59b,0x356f34e3,0xa8fd2a17,0xacb022aa,0xb4aab54d,0x358935a7,0xb267afe2,
0x354735a4,0xb52cb449,0x301226a9,0x30963364,0x32843476,0xb593b59d,0x34a032f6,0xabbd298a,0x20712f19,0xb419b50e,0x35a8355f,0xb3cdb116,0xb20eae09,0xacf5b194,0x34c73574,0xb585b4ec,
0x352535a3,0xb5a7b565,0x30b627c4,0xa2aa2ed5,0x30f6340c,0xb43db541,0x351533e7,0xb37fb033,0xad3a28fd,0xab30b175,0x3581359f,0xb596b4f5,0xb480b22b,0x31b22c24,0x32da34be,0xb4e3b590,
0x34003400,0x34003400,0x0,0x0,0x34003400,0x34003400,0x0,0x0,0x34003400,0x34003400,0x0,0x0,0x34003400,0x34003400,0x0,0x0,
0x0,0x0,0x34003400,0x34003400,0x0,0x0,0x34003400,0x34003400,0x0,0x0,0x34003400,0x34003400,0x0,0x0,0x34003400,0x34003400,
0x330e33f6,0xb30eb3f6,0xaf8ba646,0x2f8b2646,0x2ca53113,0xaca5b113,0xb3a8b22f,0x33a8322f,0xaf8ba646,0x2f8b2646,0xb30eb3f6,0x330e33f6,0xb3a8b22f,0x33a8322f,0xaca5b113,0x2ca53113,
0x2f8b2646,0xaf8ba646,0x330e33f6,0xb30eb3f6,0x33a8322f,0xb3a8b22f,0x2ca53113,0xaca5b113,0x330e33f6,0xb30eb3f6,0xaf8ba646,0x2f8b2646,0x2ca53113,0xaca5b113,0xb3a8b22f,0x33a8322f,
0x307233d9,0x307233d9,0xb2a7aa3e,0xb2a7aa3e,0xb2a7aa3e,0xb2a7aa3e,0xb072b3d9,0xb072b3d9,0xb072b3d9,0xb072b3d9,0x32a72a3e,0x32a72a3e,0x32a72a3e,0x32a72a3e,0x307233d9,0x307233d9,
0x32a72a3e,0x32a72a3e,0x307233d9,0x307233d9,0x307233d9,0x307233d9,0xb2a7aa3e,0xb2a7aa3e,0xb2a7aa3e,0xb2a7aa3e,0xb072b3d9,0xb072b3d9,0xb072b3d9,0xb072b3d9,0x32a72a3e,0x32a72a3e,
0x264633a8,0xa646b3a8,0xb3f6aca5,0x33f62ca5,0xb22fb30e,0x322f330e,0x3113af8b,0xb1132f8b,0x33f62ca5,0xb3f6aca5,0x264633a8,0xa646b3a8,0xb1132f8b,0x3113af8b,0xb22fb30e,0x322f330e,
0x33f62ca5,0xb3f6aca5,0x264633a8,0xa646b3a8,0xb1132f8b,0x3113af8b,0xb22fb30e,0x322f330e,0xa646b3a8,0x264633a8,0x33f62ca5,0xb3f6aca5,0x322f330e,0xb22fb30e,0xb1132f8b,0x3113af8b,
0xae1f3364,0xae1f3364,0xb364ae1f,0xb364ae1f,0x2e1fb364,0x2e1fb364,0x33642e1f,0x33642e1f,0xae1f3364,0xae1f3364,0xb364ae1f,0xb364ae1f,0x2e1fb364,0x2e1fb364,0x33642e1f,0x33642e1f,
0x33642e1f,0x33642e1f,0xae1f3364,0xae1f3364,0xb364ae1f,0xb364ae1f,0x2e1fb364,0x2e1fb364,0x33642e1f,0x33642e1f,0xae1f3364,0xae1f3364,0xb364ae1f,0xb364ae1f,0x2e1fb364,0x2e1fb364,
0xb22f330e,0x322fb30e,0xb113af8b,0x31132f8b,0x33f6aca5,0xb3f62ca5,0xa64633a8,0x2646b3a8,0xb113af8b,0x31132f8b,0x322fb30e,0xb22f330e,0xa64633a8,0x2646b3a8,0xb3f62ca5,0x33f6aca5,
0x31132f8b,0xb113af8b,0xb22f330e,0x322fb30e,0x2646b3a8,0xa64633a8,0x33f6aca5,0xb3f62ca5,0xb22f330e,0x322fb30e,0xb113af8b,0x31132f8b,0x33f6aca5,0xb3f62ca5,0xa64633a8,0x2646b3a8,
0xb3d932a7,0xb3d932a7,0xaa3eb072,0xaa3eb072,0x2a3e3072,0x2a3e3072,0xb3d932a7,0xb3d932a7,0x33d9b2a7,0x33d9b2a7,0x2a3e3072,0x2a3e3072,0xaa3eb072,0xaa3eb072,0x33d9b2a7,0x33d9b2a7,
0x2a3e3072,0x2a3e3072,0xb3d932a7,0xb3d932a7,0x33d9b2a7,0x33d9b2a7,0x2a3e3072,0x2a3e3072,0xaa3eb072,0xaa3eb072,0x33d9b2a7,0x33d9b2a7,0xb3d932a7,0xb3d932a7,0xaa3eb072,0xaa3eb072,
0xb3a8322f,0x33a8b22f,0x2ca5b113,0xaca53113,0xb30e33f6,0x330eb3f6,0xaf8b2646,0x2f8ba646,0xaca53113,0x2ca5b113,0xb3a8322f,0x33a8b22f,0x2f8ba646,0xaf8b2646,0xb30e33f6,0x330eb3f6,
0xaca53113,0x2ca5b113,0xb3a8322f,0x33a8b22f,0x2f8ba646,0xaf8b2646,0xb30e33f6,0x330eb3f6,0x33a8b22f,0xb3a8322f,0xaca53113,0x2ca5b113,0x330eb3f6,0xb30e33f6,0x2f8ba646,0xaf8b2646,
0xb1a831a8,0xb1a831a8,0x31a8b1a8,0x31a8b1a8,0xb1a831a8,0xb1a831a8,0x31a8b1a8,0x31a8b1a8,0xb1a831a8,0xb1a831a8,0x31a8b1a8,0x31a8b1a8,0xb1a831a8,0xb1a831a8,0x31a8b1a8,0x31a8b1a8,
0xb1a831a8,0xb1a831a8,0xb1a831a8,0xb1a831a8,0xb1a831a8,0xb1a831a8,0xb1a831a8,0xb1a831a8,0xb1a831a8,0xb1a831a8,0xb1a831a8,0xb1a831a8,0xb1a831a8,0xb1a831a8,0xb1a831a8,0xb1a831a8,
0xaca53113,0x2ca5b113,0x33a8b22f,0xb3a8322f,0x2f8ba646,0xaf8b2646,0x330eb3f6,0xb30e33f6,0x33a8b22f,0xb3a8322f,0x2ca5b113,0xaca53113,0x330eb3f6,0xb30e33f6,0xaf8b2646,0x2f8ba646,
0xb3a8322f,0x33a8b22f,0xaca53113,0x2ca5b113,0xb30e33f6,0x330eb3f6,0x2f8ba646,0xaf8b2646,0xaca53113,0x2ca5b113,0x33a8b22f,0xb3a8322f,0x2f8ba646,0xaf8b2646,0x330eb3f6,0xb30e33f6,
0x2a3e3072,0x2a3e3072,0x33d9b2a7,0x33d9b2a7,0x33d9b2a7,0x33d9b2a7,0xaa3eb072,0xaa3eb072,0xaa3eb072,0xaa3eb072,0xb3d932a7,0xb3d932a7,0xb3d932a7,0xb3d932a7,0x2a3e3072,0x2a3e3072,
0xb3d932a7,0xb3d932a7,0x2a3e3072,0x2a3e3072,0x2a3e3072,0x2a3e3072,0x33d9b2a7,0x33d9b2a7,0x33d9b2a7,0x33d9b2a7,0xaa3eb072,0xaa3eb072,0xaa3eb072,0xaa3eb072,0xb3d932a7,0xb3d932a7,
0x31132f8b,0xb113af8b,0x322fb30e,0xb22f330e,0x2646b3a8,0xa64633a8,0xb3f62ca5,0x33f6aca5,0xb22f330e,0x322fb30e,0x31132f8b,0xb113af8b,0x33f6aca5,0xb3f62ca5,0x2646b3a8,0xa64633a8,
0xb22f330e,0x322fb30e,0x31132f8b,0xb113af8b,0x33f6aca5,0xb3f62ca5,0x2646b3a8,0xa64633a8,0xb113af8b,0x31132f8b,0xb22f330e,0x322fb30e,0xa64633a8,0x2646b3a8,0x33f6aca5,0xb3f62ca5,
0x33642e1f,0x33642e1f,0x2e1fb364,0x2e1fb364,0xb364ae1f,0xb364ae1f,0xae1f3364,0xae1f3364,0x33642e1f,0x33642e1f,0x2e1fb364,0x2e1fb364,0xb364ae1f,0xb364ae1f,0xae1f3364,0xae1f3364,
0xae1f3364,0xae1f3364,0x33642e1f,0x33642e1f,0x2e1fb364,0x2e1fb364,0xb364ae1f,0xb364ae1f,0xae1f3364,0xae1f3364,0x33642e1f,0x33642e1f,0x2e1fb364,0x2e1fb364,0xb364ae1f,0xb364ae1f,
0x33f62ca5,0xb3f6aca5,0xa646b3a8,0x264633a8,0xb1132f8b,0x3113af8b,0x322f330e,0xb22fb30e,0xa646b3a8,0x264633a8,0xb3f6aca5,0x33f62ca5,0x322f330e,0xb22fb30e,0x3113af8b,0xb1132f8b,
0x264633a8,0xa646b3a8,0x33f62ca5,0xb3f6aca5,0xb22fb30e,0x322f330e,0xb1132f8b,0x3113af8b,0x33f62ca5,0xb3f6aca5,0xa646b3a8,0x264633a8,0xb1132f8b,0x3113af8b,0x322f330e,0xb22fb30e,
0x32a72a3e,0x32a72a3e,0xb072b3d9,0xb072b3d9,0x307233d9,0x307233d9,0x32a72a3e,0x32a72a3e,0xb2a7aa3e,0xb2a7aa3e,0x307233d9,0x307233d9,0xb072b3d9,0xb072b3d9,0xb2a7aa3e,0xb2a7aa3e,
0x307233d9,0x307233d9,0x32a72a3e,0x32a72a3e,0xb2a7aa3e,0xb2a7aa3e,0x307233d9,0x307233d9,0xb072b3d9,0xb072b3d9,0xb2a7aa3e,0xb2a7aa3e,0x32a72a3e,0x32a72a3e,0xb072b3d9,0xb072b3d9,
0x2f8b2646,0xaf8ba646,0xb30eb3f6,0x330e33f6,0x33a8322f,0xb3a8b22f,0xaca5b113,0x2ca53113,0x330e33f6,0xb30eb3f6,0x2f8b2646,0xaf8ba646,0x2ca53113,0xaca5b113,0x33a8322f,0xb3a8b22f,
0x330e33f6,0xb30eb3f6,0x2f8b2646,0xaf8ba646,0x2ca53113,0xaca5b113,0x33a8322f,0xb3a8b22f,0xaf8ba646,0x2f8b2646,0x330e33f6,0xb30eb3f6,0xb3a8b22f,0x33a8322f,0x2ca53113,0xaca5b113,
0x3400,0x3400,0x2f8b330e,0x2f8b330e,0x27d633f1,0xa7d6b3f1,0x309b328a,0xb09bb28a,0x2bc633c3,0x2bc633c3,0x315f31ed,0x315f31ed,0x2dc23377,0xadc2b377,0x320f313a,0xb20fb13a,
0x3400,0x3400,0x330eaf8b,0x330eaf8b,0x2fe332f6,0xafe3b2f6,0x3048b2c2,0xb04832c2,0x32dd301d,0x32dd301d,0x2248b3fe,0x2248b3fe,0x33ff1e48,0xb3ff9e48,0xaf32b325,0x2f323325,
0x3400,0x3400,0xaf8bb30e,0xaf8bb30e,0x324f30ec,0xb24fb0ec,0xb3e2a979,0x33e22979,0x33c3abc6,0x33c3abc6,0xb1ed315f,0xb1ed315f,0x2e7cb350,0xae7c3350,0x24b533fa,0xa4b5b3fa,
0x3400,0x3400,0xb30e2f8b,0xb30e2f8b,0x33b62c44,0xb3b6ac44,0x2b0333ce,0xab03b3ce,0x301db2dd,0x301db2dd,0x33fe2248,0x33fe2248,0xb184b1cb,0x318431cb,0x2d05b399,0xad053399,
0x3400,0x3400,0x2f8b330e,0x2f8b330e,0x33f1a7d6,0xb3f127d6,0x328ab09b,0xb28a309b,0xabc6b3c3,0xabc6b3c3,0xb15fb1ed,0xb15fb1ed,0xb3772dc2,0x3377adc2,0xb13a320f,0x313ab20f,
0x3400,0x3400,0x330eaf8b,0x330eaf8b,0x32f6afe3,0xb2f62fe3,0xb2c2b048,0x32c23048,0xb2ddb01d,0xb2ddb01d,0xa24833fe,0xa24833fe,0x9e4833ff,0x1e48b3ff,0x3325af32,0xb3252f32,
0x3400,0x3400,0xaf8bb30e,0xaf8bb30e,0x30ecb24f,0xb0ec324f,0xa97933e2,0x2979b3e2,0xb3c32bc6,0xb3c32bc6,0x31edb15f,0x31edb15f,0x33502e7c,0xb350ae7c,0xb3fa24b5,0x33faa4b5,
0x3400,0x3400,0xb30e2f8b,0xb30e2f8b,0x2c44b3b6,0xac4433b6,0x33ceab03,0xb3ce2b03,0xb01d32dd,0xb01d32dd,0xb3fea248,0xb3fea248,0x31cbb184,0xb1cb3184,0x33992d05,0xb399ad05,
0x32a73072,0x32a73072,0x33f62646,0x33f62646,0x33252f32,0xb325af32,0x33ff9e48,0xb3ff1e48,0x33882d64,0x33882d64,0x33eaa8b2,0x33eaa8b2,0x33ce2b03,0xb3ceab03,0x33b6ac44,0xb3b62c44,
0xb2a7b072,0xb2a7b072,0xa64633f6,0xa64633f6,0xb3faa4b5,0x33fa24b5,0x2e7c3350,0xae7cb350,0xb33b2ed7,0xb33b2ed7,0x326d30c4,0x326d30c4,0xb09b328a,0x309bb28a,0x33f127d6,0xb3f1a7d6,
0x32a73072,0x32a73072,0xb3f6a646,0xb3f6a646,0x3399ad05,0xb3992d05,0xb18431cb,0x3184b1cb,0x2d64b388,0x2d64b388,0x28b233ea,0x28b233ea,0xb048b2c2,0x304832c2,0x32f62fe3,0xb2f6afe3,
0xb2a7b072,0xb2a7b072,0x2646b3f6,0x2646b3f6,0xb20f313a,0x320fb13a,0xb377adc2,0x33772dc2,0x2ed7333b,0x2ed7333b,0xb0c4326d,0xb0c4326d,0x33e2a979,0xb3e22979,0x30ec324f,0xb0ecb24f,
0x32a73072,0x32a73072,0x33f62646,0x33f62646,0x2f32b325,0xaf323325,0x9e48b3ff,0x1e4833ff,0xb388ad64,0xb388ad64,0xb3ea28b2,0xb3ea28b2,0xab0333ce,0x2b03b3ce,0x2c4433b6,0xac44b3b6,
0xb2a7b072,0xb2a7b072,0xa64633f6,0xa64633f6,0xa4b533fa,0x24b5b3fa,0x3350ae7c,0xb3502e7c,0x333baed7,0x333baed7,0xb26db0c4,0xb26db0c4,0xb28ab09b,0x328a309b,0xa7d633f1,0x27d6b3f1,
0x32a73072,0x32a73072,0xb3f6a646,0xb3f6a646,0xad05b399,0x2d053399,0x31cb3184,0xb1cbb184,0xad643388,0xad643388,0xa8b2b3ea,0xa8b2b3ea,0x32c2b048,0xb2c23048,0xafe332f6,0x2fe3b2f6,
0xb2a7b072,0xb2a7b072,0x2646b3f6,0x2646b3f6,0x313a320f,0xb13ab20f,0xadc23377,0x2dc2b377,0xaed7b33b,0xaed7b33b,0x30c4b26d,0x30c4b26d,0x297933e2,0xa979b3e2,0xb24f30ec,0x324fb0ec,
0x34000000,0x34000000,0x330eaf8b,0x330eaf8b,0x33f1a7d6,0xb3f127d6,0x328ab09b,0xb28a309b,0x33c3abc6,0x33c3abc6,0x31edb15f,0x31edb15f,0x3377adc2,0xb3772dc2,0x313ab20f,0xb13a320f,
0x34000000,0x34000000,0xaf8bb30e,0xaf8bb30e,0x32f6afe3,0xb2f62fe3,0xb2c2b048,0x32c23048,0x301db2dd,0x301db2dd,0xb3fea248,0xb3fea248,0x1e48b3ff,0x9e4833ff,0xb3252f32,0x3325af32,
0x34000000,0x34000000,0xb30e2f8b,0xb30e2f8b,0x30ecb24f,0xb0ec324f,0xa97933e2,0x2979b3e2,0xabc6b3c3,0xabc6b3c3,0x315f31ed,0x315f31ed,0xb350ae7c,0x33502e7c,0x33faa4b5,0xb3fa24b5,
0x34000000,0x34000000,0x2f8b330e,0x2f8b330e,0x2c44b3b6,0xac4433b6,0x33ceab03,0xb3ce2b03,0xb2ddb01d,0xb2ddb01d,0x2248b3fe,0x2248b3fe,0xb1cb3184,0x31cbb184,0xb399ad05,0x33992d05,
0x34000000,0x34000000,0x330eaf8b,0x330eaf8b,0xa7d6b3f1,0x27d633f1,0xb09bb28a,0x309b328a,0xb3c32bc6,0xb3c32bc6,0xb1ed315f,0xb1ed315f,0x2dc23377,0xadc2b377,0x320f313a,0xb20fb13a,
0x34000000,0x34000000,0xaf8bb30e,0xaf8bb30e,0xafe3b2f6,0x2fe332f6,0xb04832c2,0x3048b2c2,0xb01d32dd,0xb01d32dd,0x33fe2248,0x33fe2248,0x33ff1e48,0xb3ff9e48,0xaf32b325,0x2f323325,
0x34000000,0x34000000,0xb30e2f8b,0xb30e2f8b,0xb24fb0ec,0x324f30ec,0x33e22979,0xb3e2a979,0x2bc633c3,0x2bc633c3,0xb15fb1ed,0xb15fb1ed,0x2e7cb350,0xae7c3350,0x24b533fa,0xa4b5b3fa,
0x34000000,0x34000000,0x2f8b330e,0x2f8b330e,0xb3b6ac44,0x33b62c44,0xab03b3ce,0x2b0333ce,0x32dd301d,0x32dd301d,0xa24833fe,0xa24833fe,0xb184b1cb,0x318431cb,0x2d05b399,0xad053399,
0x3072b2a7,0x3072b2a7,0x2646b3f6,0x2646b3f6,0x2f32b325,0xaf323325,0x9e48b3ff,0x1e4833ff,0x2d64b388,0x2d64b388,0xa8b2b3ea,0xa8b2b3ea,0x2b03b3ce,0xab0333ce,0xac44b3b6,0x2c4433b6,
0xb07232a7,0xb07232a7,0x33f62646,0x33f62646,0xa4b533fa,0x24b5b3fa,0x3350ae7c,0xb3502e7c,0x2ed7333b,0x2ed7333b,0x30c4b26d,0x30c4b26d,0x328a309b,0xb28ab09b,0x27d6b3f1,0xa7d633f1,
0x3072b2a7,0x3072b2a7,0xa64633f6,0xa64633f6,0xad05b399,0x2d053399,0x31cb3184,0xb1cbb184,0xb388ad64,0xb388ad64,0x33eaa8b2,0x33eaa8b2,0xb2c23048,0x32c2b048,0x2fe3b2f6,0xafe332f6,
0xb07232a7,0xb07232a7,0xb3f6a646,0xb3f6a646,0x313a320f,0xb13ab20f,0xadc23377,0x2dc2b377,0x333baed7,0x333baed7,0x326d30c4,0x326d30c4,0xa979b3e2,0x297933e2,0x324fb0ec,0xb24f30ec,
0x3072b2a7,0x3072b2a7,0x2646b3f6,0x2646b3f6,0xb325af32,0x33252f32,0xb3ff1e48,0x33ff9e48,0xad643388,0xad643388,0x28b233ea,0x28b233ea,0x33ce2b03,0xb3ceab03,0x33b6ac44,0xb3b62c44,
0xb07232a7,0xb07232a7,0x33f62646,0x33f62646,0x33fa24b5,0xb3faa4b5,0xae7cb350,0x2e7c3350,0xaed7b33b,0xaed7b33b,0xb0c4326d,0xb0c4326d,0xb09b328a,0x309bb28a,0x33f127d6,0xb3f1a7d6,
0x3072b2a7,0x3072b2a7,0xa64633f6,0xa64633f6,0xb3992d05,0x3399ad05,0x3184b1cb,0xb18431cb,0x33882d64,0x33882d64,0xb3ea28b2,0xb3ea28b2,0xb048b2c2,0x304832c2,0x32f62fe3,0xb2f6afe3,
0xb07232a7,0xb07232a7,0xb3f6a646,0xb3f6a646,0x320fb13a,0xb20f313a,0x33772dc2,0xb377adc2,0xb33b2ed7,0xb33b2ed7,0xb26db0c4,0xb26db0c4,0x33e2a979,0xb3e22979,0x30ec324f,0xb0ecb24f,
0x35a835a8,0x353135a8,0x1d8e0000,0x307d0000,0x35a735a7,0x2fb033c0,0x242a218d,0x3552341f,0x35a435a5,0xb11ea58d,0x26ef258d,0x350c35a5,0x35a035a2,0xb56eb45a,0x28da2829,0x2e5e333b,
0x35a535a8,0x351335a8,0x25d40000,0x30fe0000,0x358d359c,0x2c7c32e8,0x2c5929d1,0x358b347b,0x355e3578,0xb36badc4,0x2f2a2dc4,0x34463578,0x3517353d,0xb5a6b536,0x30ee3044,0xa5463065,
0x359f35a8,0x34f335a8,0x29200000,0x317c0000,0x35553583,0x24b831fe,0x2f8f2d18,0x35a634cc,0x34c53515,0xb4a3b0f6,0x321530f6,0x327c3515,0x33ed3465,0xb535b5a0,0x34093320,0xb06d28b6,
0x359535a8,0x34cf35a8,0x2b530000,0x31f70000,0x34ff355c,0xa84c3106,0x314d2f3b,0x35a23511,0x33c73480,0xb549b2da,0x341c32da,0x300a3480,0x30be3258,0xb428b58e,0x352334af,0xb3adac47,
0x358835a8,0x34a835a8,0x2cc10000,0x326e0000,0x348e3528,0xad6e3002,0x32b630a6,0x357e354a,0x318c337f,0xb59eb43d,0x34ee343d,0x2967337f,0x28052eb3,0xb13eb501,0x35a23567,0xb503b146,
0x357735a8,0x347e35a8,0x2dd60000,0x32e10000,0x340334e8,0xb04c2de7,0x33fa31a3,0x353c3576,0x2df831b2,0xb59db4e3,0x357534e3,0xa9ad31b2,0xadb31871,0xaa3ab406,0x357935a8,0xb59ab3f3,
0x356335a8,0x345135a8,0x2ee60000,0x33500000,0x32c4349b,0xb1c92b77,0x34893292,0x34dc3594,0x1fc62f5c,0xb546b559,0x35a83559,0xb01b2f5c,0xb25fae6f,0x2c9eb165,0x34ad356c,0xb58ab4f9,
0x354c35a8,0x342235a8,0x2ff30000,0x33ba0000,0x315d3443,0xb327261b,0x34fb3371,0x346235a5,0xad072a17,0xb49db59b,0x3584359b,0xb28b2a17,0xb493b23a,0x31e8ac8d,0x32a834b9,0xb4d3b58b,
0x3c003c00,0x0,0x0,0x3c003c00,0x3c003c00,0x0,0x0,0x3c003c00,0x3c003c00,0x0,0x0,0x3c003c00,0x3c003c00,0x0,0x0,0x3c003c00,
0x39a83c00,0x39a80000,0xb9a80000,0x39a83c00,0xb9a80000,0x39a83c00,0xb9a8bc00,0xb9a80000,0xb9a8bc00,0xb9a80000,0x39a80000,0xb9a8bc00,0x39a80000,0xb9a8bc00,0x39a83c00,0x39a80000,
0x3c00,0x3c000000,0xbc000000,0x3c00,0xbc00,0xbc000000,0x3c000000,0xbc00,0x3c00,0x3c000000,0xbc000000,0x3c00,0xbc00,0xbc000000,0x3c000000,0xbc00,
0xb9a83c00,0x39a80000,0xb9a80000,0xb9a83c00,0x39a80000,0x39a8bc00,0xb9a83c00,0x39a80000,0x39a8bc00,0xb9a80000,0x39a80000,0x39a8bc00,0xb9a80000,0xb9a83c00,0x39a8bc00,0xb9a80000,
0xbc003c00,0x0,0x0,0xbc003c00,0xbc003c00,0x0,0x0,0xbc003c00,0xbc003c00,0x0,0x0,0xbc003c00,0xbc003c00,0x0,0x0,0xbc003c00,
0xb9a83c00,0xb9a80000,0x39a80000,0xb9a83c00,0x39a80000,0xb9a83c00,0x39a8bc00,0x39a80000,0x39a8bc00,0x39a80000,0xb9a80000,0x39a8bc00,0xb9a80000,0x39a8bc00,0xb9a83c00,0xb9a80000,
0x3c00,0xbc000000,0x3c000000,0x3c00,0xbc00,0x3c000000,0xbc000000,0xbc00,0x3c00,0xbc000000,0x3c000000,0x3c00,0xbc00,0x3c000000,0xbc000000,0xbc00,
0x39a83c00,0xb9a80000,0x39a80000,0x39a83c00,0xb9a80000,0xb9a8bc00,0x39a83c00,0xb9a80000,0xb9a8bc00,0x39a80000,0xb9a80000,0xb9a8bc00,0x39a80000,0x39a83c00,0xb9a8bc00,0x39a80000,
0x3c003c00,0x0,0x0,0x3c003c00,0x3c003c00,0x0,0x0,0x3c003c00,0x3c003c00,0x0,0x0,0x3c003c00,0x3c003c00,0x0,0x0,0x3c003c00,
0x39a83c00,0x39a80000,0xb9a80000,0x39a83c00,0xb9a80000,0x39a83c00,0xb9a8bc00,0xb9a80000,0xb9a8bc00,0xb9a80000,0x39a80000,0xb9a8bc00,0x39a80000,0xb9a8bc00,0x39a83c00,0x39a80000,
0x3c00,0x3c000000,0xbc000000,0x3c00,0xbc00,0xbc000000,0x3c000000,0xbc00,0x3c00,0x3c000000,0xbc000000,0x3c00,0xbc00,0xbc000000,0x3c000000,0xbc00,
0xb9a83c00,0x39a80000,0xb9a80000,0xb9a83c00,0x39a80000,0x39a8bc00,0xb9a83c00,0x39a80000,0x39a8bc00,0xb9a80000,0x39a80000,0x39a8bc00,0xb9a80000,0xb9a83c00,0x39a8bc00,0xb9a80000,
0xbc003c00,0x0,0x0,0xbc003c00,0xbc003c00,0x0,0x0,0xbc003c00,0xbc003c00,0x0,0x0,0xbc003c00,0xbc003c00,0x0,0x0,0xbc003c00,
0xb9a83c00,0xb9a80000,0x39a80000,0xb9a83c00,0x39a80000,0xb9a83c00,0x39a8bc00,0x39a80000,0x39a8bc00,0x39a80000,0xb9a80000,0x39a8bc00,0xb9a80000,0x39a8bc00,0xb9a83c00,0xb9a80000,
0x3c00,0xbc000000,0x3c000000,0x3c00,0xbc00,0x3c000000,0xbc000000,0xbc00,0x3c00,0xbc000000,0x3c000000,0x3c00,0xbc00,0x3c000000,0xbc000000,0xbc00,
0x39a83c00,0xb9a80000,0x39a80000,0x39a83c00,0xb9a80000,0xb9a8bc00,0x39a83c00,0xb9a80000,0xb9a8bc00,0x39a80000,0xb9a80000,0xb9a8bc00,0x39a80000,0x39a83c00,0xb9a8bc00,0x39a80000,
0x35a835a8,0x35a835a8,0x0,0x0,0x35a835a8,0x35a835a8,0x0,0x0,0x35a835a8,0x35a835a8,0x0,0x0,0x35a835a8,0x35a835a8,0x0,0x0,
0x35a535a8,0x35133531,0x25d41d8e,0x30fe307d,0x3595359f,0x34cf34f3,0x2b532920,0x31f7317c,0x35773588,0x347e34a8,0x2dd62cc1,0x32e1326e,0x354c3563,0x34223451,0x2ff32ee6,0x33ba3350,
0x359c35a7,0x32e833c0,0x29d1218d,0x347b341f,0x355c3583,0x310631fe,0x2f3b2d18,0x351134cc,0x34e83528,0x2de73002,0x31a330a6,0x3576354a,0x3443349b,0x261b2b77,0x33713292,0x35a53594,
0x358d35a7,0x2c7c2fb0,0x2c59242a,0x358b3552,0x34ff3555,0xa84c24b8,0x314d2f8f,0x35a235a6,0x3403348e,0xb04cad6e,0x33fa32b6,0x353c357e,0x315d32c4,0xb327b1c9,0x34fb3489,0x346234dc,
0x357835a5,0xadc4a58d,0x2dc4258d,0x357835a5,0x34803515,0xb2dab0f6,0x32da30f6,0x34803515,0x31b2337f,0xb4e3b43d,0x34e3343d,0x31b2337f,0x2a172f5c,0xb59bb559,0x359b3559,0x2a172f5c,
0x355e35a4,0xb36bb11e,0x2f2a26ef,0x3446350c,0x33c734c5,0xb549b4a3,0x341c3215,0x300a327c,0x2df8318c,0xb59db59e,0x357534ee,0xa9ad2967,0xad071fc6,0xb49db546,0x358435a8,0xb28bb01b,
0x353d35a2,0xb536b45a,0x30442829,0x3065333b,0x32583465,0xb58eb5a0,0x34af3320,0xac4728b6,0x18712eb3,0xb406b501,0x35a83567,0xb3f3b146,0xb23aae6f,0xac8db165,0x34b9356c,0xb58bb4f9,
0x351735a0,0xb5a6b56e,0x30ee28da,0xa5462e5e,0x30be33ed,0xb428b535,0x35233409,0xb3adb06d,0xadb32805,0xaa3ab13e,0x357935a2,0xb59ab503,0xb493b25f,0x31e82c9e,0x32a834ad,0xb4d3b58a,
0x34003400,0x34003400,0x0,0x0,0x34003400,0x34003400,0x0,0x0,0x34003400,0x34003400,0x0,0x0,0x34003400,0x34003400,0x0,0x0,
0x0,0x0,0x34003400,0x34003400,0x0,0x0,0x34003400,0x34003400,0x0,0x0,0x34003400,0x34003400,0x0,0x0,0x34003400,0x34003400,
0x32f633f1,0xb2f6b3f1,0xafe3a7d6,0x2fe327d6,0x2c4430ec,0xac44b0ec,0xb3b6b24f,0x33b6324f,0xafe3a7d6,0x2fe327d6,0xb2f6b3f1,0x32f633f1,0xb3b6b24f,0x33b6324f,0xac44b0ec,0x2c4430ec,
0x2fe327d6,0xafe3a7d6,0x32f633f1,0xb2f6b3f1,0x33b6324f,0xb3b6b24f,0x2c4430ec,0xac44b0ec,0x32f633f1,0xb2f6b3f1,0xafe3a7d6,0x2fe327d6,0x2c4430ec,0xac44b0ec,0xb3b6b24f,0x33b6324f,
0x301d33c3,0x301d33c3,0xb2ddabc6,0xb2ddabc6,0xb2ddabc6,0xb2ddabc6,0xb01db3c3,0xb01db3c3,0xb01db3c3,0xb01db3c3,0x32dd2bc6,0x32dd2bc6,0x32dd2bc6,0x32dd2bc6,0x301d33c3,0x301d33c3,
0x32dd2bc6,0x32dd2bc6,0x301d33c3,0x301d33c3,0x301d33c3,0x301d33c3,0xb2ddabc6,0xb2ddabc6,0xb2ddabc6,0xb2ddabc6,0xb01db3c3,0xb01db3c3,0xb01db3c3,0xb01db3c3,0x32dd2bc6,0x32dd2bc6,
0x1e483377,0x9e48b377,0xb3ffadc2,0x33ff2dc2,0xb1cbb350,0x31cb3350,0x3184ae7c,0xb1842e7c,0x33ff2dc2,0xb3ffadc2,0x1e483377,0x9e48b377,0xb1842e7c,0x3184ae7c,0xb1cbb350,0x31cb3350,
0x33ff2dc2,0xb3ffadc2,0x1e483377,0x9e48b377,0xb1842e7c,0x3184ae7c,0xb1cbb350,0x31cb3350,0x9e48b377,0x1e483377,0x33ff2dc2,0xb3ffadc2,0x31cb3350,0xb1cbb350,0xb1842e7c,0x3184ae7c,
0xaf8b330e,0xaf8b330e,0xb30eaf8b,0xb30eaf8b,0x2f8bb30e,0x2f8bb30e,0x330e2f8b,0x330e2f8b,0xaf8b330e,0xaf8b330e,0xb30eaf8b,0xb30eaf8b,0x2f8bb30e,0x2f8bb30e,0x330e2f8b,0x330e2f8b,
0x330e2f8b,0x330e2f8b,0xaf8b330e,0xaf8b330e,0xb30eaf8b,0xb30eaf8b,0x2f8bb30e,0x2f8bb30e,0x330e2f8b,0x330e2f8b,0xaf8b330e,0xaf8b330e,0xb30eaf8b,0xb30eaf8b,0x2f8bb30e,0x2f8bb30e,
0xb2c2328a,0x32c2b28a,0xb048b09b,0x3048309b,0x33cea979,0xb3ce2979,0xab0333e2,0x2b03b3e2,0xb048b09b,0x3048309b,0x32c2b28a,0xb2c2328a,0xab0333e2,0x2b03b3e2,0xb3ce2979,0x33cea979,
0x3048309b,0xb048b09b,0xb2c2328a,0x32c2b28a,0x2b03b3e2,0xab0333e2,0x33cea979,0xb3ce2979,0xb2c2328a,0x32c2b28a,0xb048b09b,0x3048309b,0x33cea979,0xb3ce2979,0xab0333e2,0x2b03b3e2,
0xb3fe31ed,0xb3fe31ed,0xa248b15f,0xa248b15f,0x2248315f,0x2248315f,0xb3fe31ed,0xb3fe31ed,0x33feb1ed,0x33feb1ed,0x2248315f,0x2248315f,0xa248b15f,0xa248b15f,0x33feb1ed,0x33feb1ed,
0x2248315f,0x2248315f,0xb3fe31ed,0xb3fe31ed,0x33feb1ed,0x33feb1ed,0x2248315f,0x2248315f,0xa248b15f,0xa248b15f,0x33feb1ed,0x33feb1ed,0xb3fe31ed,0xb3fe31ed,0xa248b15f,0xa248b15f,
0xb325313a,0x3325b13a,0x2f32b20f,0xaf32320f,0xb39933fa,0x3399b3fa,0xad05a4b5,0x2d0524b5,0xaf32320f,0x2f32b20f,0xb325313a,0x3325b13a,0x2d0524b5,0xad05a4b5,0xb39933fa,0x3399b3fa,
0xaf32320f,0x2f32b20f,0xb325313a,0x3325b13a,0x2d0524b5,0xad05a4b5,0xb39933fa,0x3399b3fa,0x3325b13a,0xb325313a,0xaf32320f,0x2f32b20f,0x3399b3fa,0xb39933fa,0x2d0524b5,0xad05a4b5,
0xb0723072,0xb0723072,0x32a7b2a7,0x32a7b2a7,0xb0723072,0xb0723072,0x32a7b2a7,0x32a7b2a7,0xb0723072,0xb0723072,0x32a7b2a7,0x32a7b2a7,0xb0723072,0xb0723072,0x32a7b2a7,0x32a7b2a7,
0xb2a732a7,0xb2a732a7,0xb0723072,0xb0723072,0xb2a732a7,0xb2a732a7,0xb0723072,0xb0723072,0xb2a732a7,0xb2a732a7,0xb0723072,0xb0723072,0xb2a732a7,0xb2a732a7,0xb0723072,0xb0723072,
0xa4b52f32,0x24b5af32,0x33fab325,0xb3fa3325,0x313aad05,0xb13a2d05,0x320fb399,0xb20f3399,0x33fab325,0xb3fa3325,0x24b5af32,0xa4b52f32,0x320fb399,0xb20f3399,0xb13a2d05,0x313aad05,
0xb3fa3325,0x33fab325,0xa4b52f32,0x24b5af32,0xb20f3399,0x320fb399,0x313aad05,0xb13a2d05,0xa4b52f32,0x24b5af32,0x33fab325,0xb3fa3325,0x313aad05,0xb13a2d05,0x320fb399,0xb20f3399,
0x2ed72d64,0x2ed72d64,0x333bb388,0x333bb388,0x333bb388,0x333bb388,0xaed7ad64,0xaed7ad64,0xaed7ad64,0xaed7ad64,0xb33b3388,0xb33b3388,0xb33b3388,0xb33b3388,0x2ed72d64,0x2ed72d64,
0xb33b3388,0xb33b3388,0x2ed72d64,0x2ed72d64,0x2ed72d64,0x2ed72d64,0x333bb388,0x333bb388,0x333bb388,0x333bb388,0xaed7ad64,0xaed7ad64,0xaed7ad64,0xaed7ad64,0xb33b3388,0xb33b3388,
0x328a2b03,0xb28aab03,0x309bb3ce,0xb09b33ce,0xa979b2c2,0x297932c2,0xb3e23048,0x33e2b048,0xb09b33ce,0x309bb3ce,0x328a2b03,0xb28aab03,0x33e2b048,0xb3e23048,0xa979b2c2,0x297932c2,
0xb09b33ce,0x309bb3ce,0x328a2b03,0xb28aab03,0x33e2b048,0xb3e23048,0xa979b2c2,0x297932c2,0xb28aab03,0x328a2b03,0xb09b33ce,0x309bb3ce,0x297932c2,0xa979b2c2,0x33e2b048,0xb3e23048,
0x33f62646,0x33f62646,0x2646b3f6,0x2646b3f6,0xb3f6a646,0xb3f6a646,0xa64633f6,0xa64633f6,0x33f62646,0x33f62646,0x2646b3f6,0x2646b3f6,0xb3f6a646,0xb3f6a646,0xa64633f6,0xa64633f6,
0xa64633f6,0xa64633f6,0x33f62646,0x33f62646,0x2646b3f6,0x2646b3f6,0xb3f6a646,0xb3f6a646,0xa64633f6,0xa64633f6,0x33f62646,0x33f62646,0x2646b3f6,0x2646b3f6,0xb3f6a646,0xb3f6a646,
0x33509e48,0xb3501e48,0xae7cb3ff,0x2e7c33ff,0xadc231cb,0x2dc2b1cb,0x33773184,0xb377b184,0xae7cb3ff,0x2e7c33ff,0xb3501e48,0x33509e48,0x33773184,0xb377b184,0x2dc2b1cb,0xadc231cb,
0x2e7c33ff,0xae7cb3ff,0x33509e48,0xb3501e48,0xb377b184,0x33773184,0xadc231cb,0x2dc2b1cb,0x33509e48,0xb3501e48,0xae7cb3ff,0x2e7c33ff,0xadc231cb,0x2dc2b1cb,0x33773184,0xb377b184,
0x30c4a8b2,0x30c4a8b2,0xb26db3ea,0xb26db3ea,0x326d33ea,0x326d33ea,0x30c4a8b2,0x30c4a8b2,0xb0c428b2,0xb0c428b2,0x326d33ea,0x326d33ea,0xb26db3ea,0xb26db3ea,0xb0c428b2,0xb0c428b2,
0x326d33ea,0x326d33ea,0x30c4a8b2,0x30c4a8b2,0xb0c428b2,0xb0c428b2,0x326d33ea,0x326d33ea,0xb26db3ea,0xb26db3ea,0xb0c428b2,0xb0c428b2,0x30c4a8b2,0x30c4a8b2,0xb26db3ea,0xb26db3ea,
0x27d6ac44,0xa7d62c44,0xb3f1b3b6,0x33f133b6,0x324f2fe3,0xb24fafe3,0xb0ecb2f6,0x30ec32f6,0x33f133b6,0xb3f1b3b6,0x27d6ac44,0xa7d62c44,0x30ec32f6,0xb0ecb2f6,0x324f2fe3,0xb24fafe3,
0x33f133b6,0xb3f1b3b6,0x27d6ac44,0xa7d62c44,0x30ec32f6,0xb0ecb2f6,0x324f2fe3,0xb24fafe3,0xa7d62c44,0x27d6ac44,0x33f133b6,0xb3f1b3b6,0xb24fafe3,0x324f2fe3,0x30ec32f6,0xb0ecb2f6,
0x3400,0x3400,0x307232a7,0x307232a7,0x28b233ea,0xa8b2b3ea,0x315f31ed,0xb15fb1ed,0x2ca533a8,0x2ca533a8,0x322f3113,0x322f3113,0x2ed7333b,0xaed7b33b,0x32dd301d,0xb2ddb01d,
0x3400,0x3400,0x32a7b072,0x32a7b072,0x301d32dd,0xb01db2dd,0x2ed7b33b,0xaed7333b,0x330e2f8b,0x330e2f8b,0xa646b3f6,0xa646b3f6,0x33fea248,0xb3fe2248,0xb0c4b26d,0x30c4326d,
0x3400,0x3400,0xb072b2a7,0xb072b2a7,0x326d30c4,0xb26db0c4,0xb3fea248,0x33fe2248,0x33a8aca5,0x33a8aca5,0xb113322f,0xb113322f,0x2d64b388,0xad643388,0x2bc633c3,0xabc6b3c3,
0x3400,0x3400,0xb2a73072,0xb2a73072,0x33c32bc6,0xb3c3abc6,0x2d643388,0xad64b388,0x2f8bb30e,0x2f8bb30e,0x33f6a646,0x33f6a646,0xb1edb15f,0x31ed315f,0x28b2b3ea,0xa8b233ea,
0x3400,0x3400,0x307232a7,0x307232a7,0x33eaa8b2,0xb3ea28b2,0x31edb15f,0xb1ed315f,0xaca5b3a8,0xaca5b3a8,0xb22fb113,0xb22fb113,0xb33b2ed7,0x333baed7,0xb01d32dd,0x301db2dd,
0x3400,0x3400,0x32a7b072,0x32a7b072,0x32ddb01d,0xb2dd301d,0xb33baed7,0x333b2ed7,0xb30eaf8b,0xb30eaf8b,0x264633f6,0x264633f6,0x224833fe,0xa248b3fe,0x326db0c4,0xb26d30c4,
0x3400,0x3400,0xb072b2a7,0xb072b2a7,0x30c4b26d,0xb0c4326d,0xa24833fe,0x2248b3fe,0xb3a82ca5,0xb3a82ca5,0x3113b22f,0x3113b22f,0x33882d64,0xb388ad64,0xb3c32bc6,0x33c3abc6,
0x3400,0x3400,0xb2a73072,0xb2a73072,0x2bc6b3c3,0xabc633c3,0x3388ad64,0xb3882d64,0xaf8b330e,0xaf8b330e,0xb3f62646,0xb3f62646,0x315fb1ed,0xb15f31ed,0x33ea28b2,0xb3eaa8b2,
0x33642e1f,0x33642e1f,0x33d9aa3e,0x33d9aa3e,0x33c32bc6,0xb3c3abc6,0x3388ad64,0xb3882d64,0x33f62646,0x33f62646,0x330eaf8b,0x330eaf8b,0x33fea248,0xb3fe2248,0x326db0c4,0xb26d30c4,
0xb364ae1f,0xb364ae1f,0x2a3e33d9,0x2a3e33d9,0xb3ea28b2,0x33eaa8b2,0x315f31ed,0xb15fb1ed,0xb22f3113,0xb22f3113,0x33a82ca5,0x33a82ca5,0xad643388,0x2d64b388,0x33c3abc6,0xb3c32bc6,
0x33642e1f,0x33642e1f,0xb3d92a3e,0xb3d92a3e,0x32ddb01d,0xb2dd301d,0xaed7333b,0x2ed7b33b,0x2646b3f6,0x2646b3f6,0x2f8b330e,0x2f8b330e,0xb1edb15f,0x31ed315f,0x33ea28b2,0xb3eaa8b2,
0xb364ae1f,0xb364ae1f,0xaa3eb3d9,0xaa3eb3d9,0xb0c4326d,0x30c4b26d,0xb3fea248,0x33fe2248,0x3113322f,0x3113322f,0xaca533a8,0xaca533a8,0x333baed7,0xb33b2ed7,0x32dd301d,0xb2ddb01d,
0x33642e1f,0x33642e1f,0x33d9aa3e,0x33d9aa3e,0x2bc6b3c3,0xabc633c3,0xad64b388,0x2d643388,0xb3f6a646,0xb3f6a646,0xb30e2f8b,0xb30e2f8b,0x224833fe,0xa248b3fe,0x30c4326d,0xb0c4b26d,
0xb364ae1f,0xb364ae1f,0x2a3e33d9,0x2a3e33d9,0x28b233ea,0xa8b2b3ea,0x31edb15f,0xb1ed315f,0x322fb113,0x322fb113,0xb3a8aca5,0xb3a8aca5,0xb388ad64,0x33882d64,0x2bc633c3,0xabc6b3c3,
0x33642e1f,0x33642e1f,0xb3d92a3e,0xb3d92a3e,0xb01db2dd,0x301d32dd,0x333b2ed7,0xb33baed7,0xa64633f6,0xa64633f6,0xaf8bb30e,0xaf8bb30e,0x315fb1ed,0xb15f31ed,0xa8b233ea,0x28b2b3ea,
0xb364ae1f,0xb364ae1f,0xaa3eb3d9,0xaa3eb3d9,0x326d30c4,0xb26db0c4,0xa24833fe,0x2248b3fe,0xb113b22f,0xb113b22f,0x2ca5b3a8,0x2ca5b3a8,0x2ed7333b,0xaed7b33b,0xb01d32dd,0x301db2dd,
0x34000000,0x34000000,0x32a7b072,0x32a7b072,0x33eaa8b2,0xb3ea28b2,0x31edb15f,0xb1ed315f,0x33a8aca5,0x33a8aca5,0x3113b22f,0x3113b22f,0x333baed7,0xb33b2ed7,0x301db2dd,0xb01d32dd,
0x34000000,0x34000000,0xb072b2a7,0xb072b2a7,0x32ddb01d,0xb2dd301d,0xb33baed7,0x333b2ed7,0x2f8bb30e,0x2f8bb30e,0xb3f62646,0xb3f62646,0xa248b3fe,0x224833fe,0xb26d30c4,0x326db0c4,
0x34000000,0x34000000,0xb2a73072,0xb2a73072,0x30c4b26d,0xb0c4326d,0xa24833fe,0x2248b3fe,0xaca5b3a8,0xaca5b3a8,0x322f3113,0x322f3113,0xb388ad64,0x33882d64,0x33c3abc6,0xb3c32bc6,
0x34000000,0x34000000,0x307232a7,0x307232a7,0x2bc6b3c3,0xabc633c3,0x3388ad64,0xb3882d64,0xb30eaf8b,0xb30eaf8b,0xa646b3f6,0xa646b3f6,0xb15f31ed,0x315fb1ed,0xb3eaa8b2,0x33ea28b2,
0x34000000,0x34000000,0x32a7b072,0x32a7b072,0xa8b2b3ea,0x28b233ea,0xb15fb1ed,0x315f31ed,0xb3a82ca5,0xb3a82ca5,0xb113322f,0xb113322f,0x2ed7333b,0xaed7b33b,0x32dd301d,0xb2ddb01d,
0x34000000,0x34000000,0xb072b2a7,0xb072b2a7,0xb01db2dd,0x301d32dd,0xaed7333b,0x2ed7b33b,0xaf8b330e,0xaf8b330e,0x33f6a646,0x33f6a646,0x33fea248,0xb3fe2248,0xb0c4b26d,0x30c4326d,
0x34000000,0x34000000,0xb2a73072,0xb2a73072,0xb26db0c4,0x326d30c4,0x33fe2248,0xb3fea248,0x2ca533a8,0x2ca533a8,0xb22fb113,0xb22fb113,0x2d64b388,0xad643388,0x2bc633c3,0xabc6b3c3,
0x34000000,0x34000000,0x307232a7,0x307232a7,0xb3c3abc6,0x33c32bc6,0xad64b388,0x2d643388,0x330e2f8b,0x330e2f8b,0x264633f6,0x264633f6,0xb1edb15f,0x31ed315f,0x28b2b3ea,0xa8b233ea,
0x2e1fb364,0x2e1fb364,0xaa3eb3d9,0xaa3eb3d9,0x2bc6b3c3,0xabc633c3,0xad64b388,0x2d643388,0x2646b3f6,0x2646b3f6,0xaf8bb30e,0xaf8bb30e,0xa248b3fe,0x224833fe,0xb0c4b26d,0x30c4326d,
0xae1f3364,0xae1f3364,0x33d9aa3e,0x33d9aa3e,0x28b233ea,0xa8b2b3ea,0x31edb15f,0xb1ed315f,0x3113322f,0x3113322f,0x2ca5b3a8,0x2ca5b3a8,0x33882d64,0xb388ad64,0xabc6b3c3,0x2bc633c3,
0x2e1fb364,0x2e1fb364,0x2a3e33d9,0x2a3e33d9,0xb01db2dd,0x301d32dd,0x333b2ed7,0xb33baed7,0xb3f6a646,0xb3f6a646,0x330eaf8b,0x330eaf8b,0xb15f31ed,0x315fb1ed,0x28b2b3ea,0xa8b233ea,
0xae1f3364,0xae1f3364,0xb3d92a3e,0xb3d92a3e,0x326d30c4,0xb26db0c4,0xa24833fe,0x2248b3fe,0x322fb113,0x322fb113,0x33a82ca5,0x33a82ca5,0xaed7b33b,0x2ed7333b,0x301db2dd,0xb01d32dd,
0x2e1fb364,0x2e1fb364,0xaa3eb3d9,0xaa3eb3d9,0xb3c3abc6,0x33c32bc6,0xb3882d64,0x3388ad64,0xa64633f6,0xa64633f6,0x2f8b330e,0x2f8b330e,0x33fea248,0xb3fe2248,0x326db0c4,0xb26d30c4,
0xae1f3364,0xae1f3364,0x33d9aa3e,0x33d9aa3e,0x33eaa8b2,0xb3ea28b2,0xb15fb1ed,0x315f31ed,0xb113b22f,0xb113b22f,0xaca533a8,0xaca533a8,0xad643388,0x2d64b388,0x33c3abc6,0xb3c32bc6,
0x2e1fb364,0x2e1fb364,0x2a3e33d9,0x2a3e33d9,0xb2dd301d,0x32ddb01d,0x2ed7b33b,0xaed7333b,0x33f62646,0x33f62646,0xb30e2f8b,0xb30e2f8b,0xb1edb15f,0x31ed315f,0x33ea28b2,0xb3eaa8b2,
0xae1f3364,0xae1f3364,0xb3d92a3e,0xb3d92a3e,0x30c4b26d,0xb0c4326d,0x33fe2248,0xb3fea248,0xb22f3113,0xb22f3113,0xb3a8aca5,0xb3a8aca5,0x333baed7,0xb33b2ed7,0x32dd301d,0xb2ddb01d,
0x35a835a8,0x352f35a8,0x1eaa0000,0x30850000,0x35a635a7,0x2f7e33b3,0x24ff22aa,0x35563425,0x35a235a4,0xb146a6a9,0x282926a9,0x350135a4,0x359c359f,0xb576b46b,0x29d128fd,0x2de73312,
0x35a535a8,0x351135a8,0x261b0000,0x31060000,0x358b359b,0x2c4732da,0x2c8d2a17,0x358e3480,0x35563574,0xb38cae09,0x2f7e2e09,0x34373574,0x350a3533,0xb5a4b541,0x31263075,0xa7363033,
0x359e35a8,0x34f035a8,0x29440000,0x31840000,0x35503581,0x23c631ef,0x2fc12d3a,0x35a734d1,0x34b9350e,0xb4afb116,0x323a3116,0x3258350e,0x33c03454,0xb528b5a3,0x341f3349,0xb0a627c4,
0x359435a8,0x34cc35a8,0x2b770000,0x31fe0000,0x34f93559,0xa8b630f6,0x31652f5c,0x35a03515,0x33a63476,0xb550b2f6,0x342b32f6,0x2fc13476,0x3085322b,0xb413b589,0x352f34be,0xb3daacb0,
0x358735a8,0x34a535a8,0x2cd20000,0x32750000,0x34863525,0xada22fe2,0x32cc30b6,0x357b354d,0x31653364,0xb5a0b449,0x34f93449,0x28b63364,0x261b2e4d,0xb106b4f5,0x35a5356f,0xb511b175,
0x357635a8,0x347b35a8,0x2de70000,0x32e80000,0x33f334e3,0xb0652dc4,0x340631b2,0x35363578,0x2da23194,0xb59ab4ec,0x357b34ec,0xaa5e3194,0xae2b9c71,0xa944b3e7,0x357135a8,0xb59eb40c,
0x356235a8,0x344e35a8,0x2ef70000,0x33560000,0x32af3496,0xb1e02b30,0x349032a1,0x34d63596,0x18712f19,0xb53db55f,0x35a8355f,0xb0442f19,0xb292aed5,0x2d18b136,0x349b3565,0xb583b505,
0x354a35a8,0x341f35a8,0x30020000,0x33c00000,0x3146343d,0xb33b258d,0x3501337f,0x345a35a5,0xad5d298a,0xb490b59d,0x357f359d,0xb2af298a,0xb4a5b267,0x321dac24,0x327534aa,0xb4c3b590,
0x3c003c00,0x0,0x0,0x3c003c00,0x3c003c00,0x0,0x0,0x3c003c00,0x3c003c00,0x0,0x0,0x3c003c00,0x3c003c00,0x0,0x0,0x3c003c00,
0x39a83c00,0x39a80000,0xb9a80000,0x39a83c00,0xb9a80000,0x39a83c00,0xb9a8bc00,0xb9a80000,0xb9a8bc00,0xb9a80000,0x39a80000,0xb9a8bc00,0x39a80000,0xb9a8bc00,0x39a83c00,0x39a80000,
0x3c00,0x3c000000,0xbc000000,0x3c00,0xbc00,0xbc000000,0x3c000000,0xbc00,0x3c00,0x3c000000,0xbc000000,0x3c00,0xbc00,0xbc000000,0x3c000000,0xbc00,
0xb9a83c00,0x39a80000,0xb9a80000,0xb9a83c00,0x39a80000,0x39a8bc00,0xb9a83c00,0x39a80000,0x39a8bc00,0xb9a80000,0x39a80000,0x39a8bc00,0xb9a80000,0xb9a83c00,0x39a8bc00,0xb9a80000,
0xbc003c00,0x0,0x0,0xbc003c00,0xbc003c00,0x0,0x0,0xbc003c00,0xbc003c00,0x0,0x0,0xbc003c00,0xbc003c00,0x0,0x0,0xbc003c00,
0xb9a83c00,0xb9a80000,0x39a80000,0xb9a83c00,0x39a80000,0xb9a83c00,0x39a8bc00,0x39a80000,0x39a8bc00,0x39a80000,0xb9a80000,0x39a8bc00,0xb9a80000,0x39a8bc00,0xb9a83c00,0xb9a80000,
0x3c00,0xbc000000,0x3c000000,0x3c00,0xbc00,0x3c000000,0xbc000000,0xbc00,0x3c00,0xbc000000,0x3c000000,0x3c00,0xbc00,0x3c000000,0xbc000000,0xbc00,
0x39a83c00,0xb9a80000,0x39a80000,0x39a83c00,0xb9a80000,0xb9a8bc00,0x39a83c00,0xb9a80000,0xb9a8bc00,0x39a80000,0xb9a80000,0xb9a8bc00,0x39a80000,0x39a83c00,0xb9a8bc00,0x39a80000,
0x3c003c00,0x0,0x0,0x3c003c00,0x3c003c00,0x0,0x0,0x3c003c00,0x3c003c00,0x0,0x0,0x3c003c00,0x3c003c00,0x0,0x0,0x3c003c00,
0x39a83c00,0x39a80000,0xb9a80000,0x39a83c00,0xb9a80000,0x39a83c00,0xb9a8bc00,0xb9a80000,0xb9a8bc00,0xb9a80000,0x39a80000,0xb9a8bc00,0x39a80000,0xb9a8bc00,0x39a83c00,0x39a80000,
0x3c00,0x3c000000,0xbc000000,0x3c00,0xbc00,0xbc000000,0x3c000000,0xbc00,0x3c00,0x3c000000,0xbc000000,0x3c00,0xbc00,0xbc000000,0x3c000000,0xbc00,
0xb9a83c00,0x39a80000,0xb9a80000,0xb9a83c00,0x39a80000,0x39a8bc00,0xb9a83c00,0x39a80000,0x39a8bc00,0xb9a80000,0x39a80000,0x39a8bc00,0xb9a80000,0xb9a83c00,0x39a8bc00,0xb9a80000,
0xbc003c00,0x0,0x0,0xbc003c00,0xbc003c00,0x0,0x0,0xbc003c00,0xbc003c00,0x0,0x0,0xbc003c00,0xbc003c00,0x0,0x0,0xbc003c00,
0xb9a83c00,0xb9a80000,0x39a80000,0xb9a83c00,0x39a80000,0xb9a83c00,0x39a8bc00,0x39a80000,0x39a8bc00,0x39a80000,0xb9a80000,0x39a8bc00,0xb9a80000,0x39a8bc00,0xb9a83c00,0xb9a80000,
0x3c00,0xbc000000,0x3c000000,0x3c00,0xbc00,0x3c000000,0xbc000000,0xbc00,0x3c00,0xbc000000,0x3c000000,0x3c00,0xbc00,0x3c000000,0xbc000000,0xbc00,
0x39a83c00,0xb9a80000,0x39a80000,0x39a83c00,0xb9a80000,0xb9a8bc00,0x39a83c00,0xb9a80000,0xb9a8bc00,0x39a80000,0xb9a80000,0xb9a8bc00,0x39a80000,0x39a83c00,0xb9a8bc00,0x39a80000,
0x35a835a8,0x35a835a8,0x0,0x0,0x35a835a8,0x35a835a8,0x0,0x0,0x35a835a8,0x35a835a8,0x0,0x0,0x35a835a8,0x35a835a8,0x0,0x0,
0x35a535a8,0x3511352f,0x261b1eaa,0x31063085,0x3594359e,0x34cc34f0,0x2b772944,0x31fe3184,0x35763587,0x347b34a5,0x2de72cd2,0x32e83275,0x354a3562,0x341f344e,0x30022ef7,0x33c03356,
0x359b35a7,0x32da33b3,0x2a1722aa,0x34803425,0x35593581,0x30f631ef,0x2f5c2d3a,0x351534d1,0x34e33525,0x2dc42fe2,0x31b230b6,0x3578354d,0x343d3496,0x258d2b30,0x337f32a1,0x35a53596,
0x358b35a6,0x2c472f7e,0x2c8d24ff,0x358e3556,0x34f93550,0xa8b623c6,0x31652fc1,0x35a035a7,0x33f33486,0xb065ada2,0x340632cc,0x3536357b,0x314632af,0xb33bb1e0,0x35013490,0x345a34d6,
0x357435a4,0xae09a6a9,0x2e0926a9,0x357435a4,0x3476350e,0xb2f6b116,0x32f63116,0x3476350e,0x31943364,0xb4ecb449,0x34ec3449,0x31943364,0x298a2f19,0xb59db55f,0x359d355f,0x298a2f19,
0x355635a2,0xb38cb146,0x2f7e2829,0x34373501,0x33a634b9,0xb550b4af,0x342b323a,0x2fc13258,0x2da23165,0xb59ab5a0,0x357b34f9,0xaa5e28b6,0xad5d1871,0xb490b53d,0x357f35a8,0xb2afb044,
0x3533359f,0xb541b46b,0x307528fd,0x30333312,0x322b3454,0xb589b5a3,0x34be3349,0xacb027c4,0x9c712e4d,0xb3e7b4f5,0x35a8356f,0xb40cb175,0xb267aed5,0xac24b136,0x34aa3565,0xb590b505,
0x350a359c,0xb5a4b576,0x312629d1,0xa7362de7,0x308533c0,0xb413b528,0x352f341f,0xb3dab0a6,0xae2b261b,0xa944b106,0x357135a5,0xb59eb511,0xb4a5b292,0x321d2d18,0x3275349b,0xb4c3b583,
0x34003400,0x34003400,0x0,0x0,0x34003400,0x34003400,0x0,0x0,0x34003400,0x34003400,0x0,0x0,0x34003400,0x34003400,0x0,0x0,
0x0,0x0,0x34003400,0x34003400,0x0,0x0,0x34003400,0x34003400,0x0,0x0,0x34003400,0x34003400,0x0,0x0,0x34003400,0x34003400,
0x32dd33ea,0xb2ddb3ea,0xb01da8b2,0x301d28b2,0x2bc630c4,0xabc6b0c4,0xb3c3b26d,0x33c3326d,0xb01da8b2,0x301d28b2,0xb2ddb3ea,0x32dd33ea,0xb3c3b26d,0x33c3326d,0xabc6b0c4,0x2bc630c4,
0x301d28b2,0xb01da8b2,0x32dd33ea,0xb2ddb3ea,0x33c3326d,0xb3c3b26d,0x2bc630c4,0xabc6b0c4,0x32dd33ea,0xb2ddb3ea,0xb01da8b2,0x301d28b2,0x2bc630c4,0xabc6b0c4,0xb3c3b26d,0x33c3326d,
0x2f8b33a8,0x2f8b33a8,0xb30eaca5,0xb30eaca5,0xb30eaca5,0xb30eaca5,0xaf8bb3a8,0xaf8bb3a8,0xaf8bb3a8,0xaf8bb3a8,0x330e2ca5,0x330e2ca5,0x330e2ca5,0x330e2ca5,0x2f8b33a8,0x2f8b33a8,
0x330e2ca5,0x330e2ca5,0x2f8b33a8,0x2f8b33a8,0x2f8b33a8,0x2f8b33a8,0xb30eaca5,0xb30eaca5,0xb30eaca5,0xb30eaca5,0xaf8bb3a8,0xaf8bb3a8,0xaf8bb3a8,0xaf8bb3a8,0x330e2ca5,0x330e2ca5,
0xa248333b,0x2248b33b,0xb3feaed7,0x33fe2ed7,0xb15fb388,0x315f3388,0x31edad64,0xb1ed2d64,0x33fe2ed7,0xb3feaed7,0xa248333b,0x2248b33b,0xb1ed2d64,0x31edad64,0xb15fb388,0x315f3388,
0x33fe2ed7,0xb3feaed7,0xa248333b,0x2248b33b,0xb1ed2d64,0x31edad64,0xb15fb388,0x315f3388,0x2248b33b,0xa248333b,0x33fe2ed7,0xb3feaed7,0x315f3388,0xb15fb388,0xb1ed2d64,0x31edad64,
0xb07232a7,0xb07232a7,0xb2a7b072,0xb2a7b072,0x3072b2a7,0x3072b2a7,0x32a73072,0x32a73072,0xb07232a7,0xb07232a7,0xb2a7b072,0xb2a7b072,0x3072b2a7,0x3072b2a7,0x32a73072,0x32a73072,
0x32a73072,0x32a73072,0xb07232a7,0xb07232a7,0xb2a7b072,0xb2a7b072,0x3072b2a7,0x3072b2a7,0x32a73072,0x32a73072,0xb07232a7,0xb07232a7,0xb2a7b072,0xb2a7b072,0x3072b2a7,0x3072b2a7,
0xb33b31ed,0x333bb1ed,0xaed7b15f,0x2ed7315f,0x3388a248,0xb3882248,0xad6433fe,0x2d64b3fe,0xaed7b15f,0x2ed7315f,0x333bb1ed,0xb33b31ed,0xad6433fe,0x2d64b3fe,0xb3882248,0x3388a248,
0x2ed7315f,0xaed7b15f,0xb33b31ed,0x333bb1ed,0x2d64b3fe,0xad6433fe,0x3388a248,0xb3882248,0xb33b31ed,0x333bb1ed,0xaed7b15f,0x2ed7315f,0x3388a248,0xb3882248,0xad6433fe,0x2d64b3fe,
0xb3f63113,0xb3f63113,0x2646b22f,0x2646b22f,0xa646322f,0xa646322f,0xb3f63113,0xb3f63113,0x33f6b113,0x33f6b113,0xa646322f,0xa646322f,0x2646b22f,0x2646b22f,0x33f6b113,0x33f6b113,
0xa646322f,0xa646322f,0xb3f63113,0xb3f63113,0x33f6b113,0x33f6b113,0xa646322f,0xa646322f,0x2646b22f,0x2646b22f,0x33f6b113,0x33f6b113,0xb3f63113,0xb3f63113,0x2646b22f,0x2646b22f,
0xb26d301d,0x326db01d,0x30c4b2dd,0xb0c432dd,0xb3ea33c3,0x33eab3c3,0xa8b2abc6,0x28b22bc6,0xb0c432dd,0x30c4b2dd,0xb26d301d,0x326db01d,0x28b22bc6,0xa8b2abc6,0xb3ea33c3,0x33eab3c3,
0xb0c432dd,0x30c4b2dd,0xb26d301d,0x326db01d,0x28b22bc6,0xa8b2abc6,0xb3ea33c3,0x33eab3c3,0x326db01d,0xb26d301d,0xb0c432dd,0x30c4b2dd,0x33eab3c3,0xb3ea33c3,0x28b22bc6,0xa8b2abc6,
0xae1f2e1f,0xae1f2e1f,0x3364b364,0x3364b364,0xae1f2e1f,0xae1f2e1f,0x3364b364,0x3364b364,0xae1f2e1f,0xae1f2e1f,0x3364b364,0x3364b364,0xae1f2e1f,0xae1f2e1f,0x3364b364,0x3364b364,
0xb3643364,0xb3643364,0xae1f2e1f,0xae1f2e1f,0xb3643364,0xb3643364,0xae1f2e1f,0xae1f2e1f,0xb3643364,0xb3643364,0xae1f2e1f,0xae1f2e1f,0xb3643364,0xb3643364,0xae1f2e1f,0xae1f2e1f,
0x28b22bc6,0xa8b2abc6,0x33eab3c3,0xb3ea33c3,0x326db01d,0xb26d301d,0x30c4b2dd,0xb0c432dd,0x33eab3c3,0xb3ea33c3,0xa8b2abc6,0x28b22bc6,0x30c4b2dd,0xb0c432dd,0xb26d301d,0x326db01d,
0xb3ea33c3,0x33eab3c3,0x28b22bc6,0xa8b2abc6,0xb0c432dd,0x30c4b2dd,0x326db01d,0xb26d301d,0x28b22bc6,0xa8b2abc6,0x33eab3c3,0xb3ea33c3,0x326db01d,0xb26d301d,0x30c4b2dd,0xb0c432dd,
0x31132646,0x31132646,0x322fb3f6,0x322fb3f6,0x322fb3f6,0x322fb3f6,0xb113a646,0xb113a646,0xb113a646,0xb113a646,0xb22f33f6,0xb22f33f6,0xb22f33f6,0xb22f33f6,0x31132646,0x31132646,
0xb22f33f6,0xb22f33f6,0x31132646,0x31132646,0x31132646,0x31132646,0x322fb3f6,0x322fb3f6,0x322fb3f6,0x322fb3f6,0xb113a646,0xb113a646,0xb113a646,0xb113a646,0xb22f33f6,0xb22f33f6,
0x3388a248,0xb3882248,0x2d64b3fe,0xad6433fe,0xaed7b15f,0x2ed7315f,0xb33b31ed,0x333bb1ed,0xad6433fe,0x2d64b3fe,0x3388a248,0xb3882248,0x333bb1ed,0xb33b31ed,0xaed7b15f,0x2ed7315f,
0xad6433fe,0x2d64b3fe,0x3388a248,0xb3882248,0x333bb1ed,0xb33b31ed,0xaed7b15f,0x2ed7315f,0xb3882248,0x3388a248,0xad6433fe,0x2d64b3fe,0x2ed7315f,0xaed7b15f,0x333bb1ed,0xb33b31ed,
0x33d9aa3e,0x33d9aa3e,0xaa3eb3d9,0xaa3eb3d9,0xb3d92a3e,0xb3d92a3e,0x2a3e33d9,0x2a3e33d9,0x33d9aa3e,0x33d9aa3e,0xaa3eb3d9,0xaa3eb3d9,0xb3d92a3e,0xb3d92a3e,0x2a3e33d9,0x2a3e33d9,
0x2a3e33d9,0x2a3e33d9,0x33d9aa3e,0x33d9aa3e,0xaa3eb3d9,0xaa3eb3d9,0xb3d92a3e,0xb3d92a3e,0x2a3e33d9,0x2a3e33d9,0x33d9aa3e,0x33d9aa3e,0xaa3eb3d9,0xaa3eb3d9,0xb3d92a3e,0xb3d92a3e,
0x31edad64,0xb1ed2d64,0xb15fb388,0x315f3388,0xa248333b,0x2248b33b,0x33fe2ed7,0xb3feaed7,0xb15fb388,0x315f3388,0xb1ed2d64,0x31edad64,0x33fe2ed7,0xb3feaed7,0x2248b33b,0xa248333b,
0x315f3388,0xb15fb388,0x31edad64,0xb1ed2d64,0xb3feaed7,0x33fe2ed7,0xa248333b,0x2248b33b,0x31edad64,0xb1ed2d64,0xb15fb388,0x315f3388,0xa248333b,0x2248b33b,0x33fe2ed7,0xb3feaed7,
0x2ca5af8b,0x2ca5af8b,0xb3a8b30e,0xb3a8b30e,0x33a8330e,0x33a8330e,0x2ca5af8b,0x2ca5af8b,0xaca52f8b,0xaca52f8b,0x33a8330e,0x33a8330e,0xb3a8b30e,0xb3a8b30e,0xaca52f8b,0xaca52f8b,
0x33a8330e,0x33a8330e,0x2ca5af8b,0x2ca5af8b,0xaca52f8b,0xaca52f8b,0x33a8330e,0x33a8330e,0xb3a8b30e,0xb3a8b30e,0xaca52f8b,0xaca52f8b,0x2ca5af8b,0x2ca5af8b,0xb3a8b30e,0xb3a8b30e,
0xabc6b0c4,0x2bc630c4,0xb3c3b26d,0x33c3326d,0x301d28b2,0xb01da8b2,0xb2ddb3ea,0x32dd33ea,0x33c3326d,0xb3c3b26d,0xabc6b0c4,0x2bc630c4,0x32dd33ea,0xb2ddb3ea,0x301d28b2,0xb01da8b2,
0x33c3326d,0xb3c3b26d,0xabc6b0c4,0x2bc630c4,0x32dd33ea,0xb2ddb3ea,0x301d28b2,0xb01da8b2,0x2bc630c4,0xabc6b0c4,0x33c3326d,0xb3c3b26d,0xb01da8b2,0x301d28b2,0x32dd33ea,0xb2ddb3ea,
0x3400,0x3400,0x3113322f,0x3113322f,0x297933e2,0xa979b3e2,0x320f313a,0xb20fb13a,0x2d643388,0x2d643388,0x32dd301d,0x32dd301d,0x2fe332f6,0xafe3b2f6,0x33772dc2,0xb377adc2,
0x3400,0x3400,0x322fb113,0x322fb113,0x304832c2,0xb048b2c2,0x2d05b399,0xad053399,0x333b2ed7,0x333b2ed7,0xabc6b3c3,0xabc6b3c3,0x33f1a7d6,0xb3f127d6,0xb1cbb184,0x31cb3184,
0x3400,0x3400,0xb113b22f,0xb113b22f,0x328a309b,0xb28ab09b,0xb3fa24b5,0x33faa4b5,0x3388ad64,0x3388ad64,0xb01d32dd,0xb01d32dd,0x2c44b3b6,0xac4433b6,0x2e7c3350,0xae7cb350,
0x3400,0x3400,0xb22f3113,0xb22f3113,0x33ce2b03,0xb3ceab03,0x2f323325,0xaf32b325,0x2ed7b33b,0x2ed7b33b,0x33c3abc6,0x33c3abc6,0xb24fb0ec,0x324f30ec,0x9e48b3ff,0x1e4833ff,
0x3400,0x3400,0x3113322f,0x3113322f,0x33e2a979,0xb3e22979,0x313ab20f,0xb13a320f,0xad64b388,0xad64b388,0xb2ddb01d,0xb2ddb01d,0xb2f62fe3,0x32f6afe3,0xadc23377,0x2dc2b377,
0x3400,0x3400,0x322fb113,0x322fb113,0x32c2b048,0xb2c23048,0xb399ad05,0x33992d05,0xb33baed7,0xb33baed7,0x2bc633c3,0x2bc633c3,0x27d633f1,0xa7d6b3f1,0x3184b1cb,0xb18431cb,
0x3400,0x3400,0xb113b22f,0xb113b22f,0x309bb28a,0xb09b328a,0x24b533fa,0xa4b5b3fa,0xb3882d64,0xb3882d64,0x301db2dd,0x301db2dd,0x33b62c44,0xb3b6ac44,0xb3502e7c,0x3350ae7c,
0x3400,0x3400,0xb22f3113,0xb22f3113,0x2b03b3ce,0xab0333ce,0x3325af32,0xb3252f32,0xaed7333b,0xaed7333b,0xb3c32bc6,0xb3c32bc6,0x30ecb24f,0xb0ec324f,0x33ff9e48,0xb3ff1e48,
0x33d92a3e,0x33d92a3e,0x330eaf8b,0x330eaf8b,0x33ff1e48,0xb3ff9e48,0x324fb0ec,0xb24f30ec,0x33eaa8b2,0x33eaa8b2,0x315fb1ed,0x315fb1ed,0x3399ad05,0xb3992d05,0x3048b2c2,0xb04832c2,
0xb3d9aa3e,0xb3d9aa3e,0x2f8b330e,0x2f8b330e,0xb3772dc2,0x3377adc2,0x32f62fe3,0xb2f6afe3,0xb0c4326d,0xb0c4326d,0x33fea248,0x33fea248,0xa4b533fa,0x24b5b3fa,0x328ab09b,0xb28a309b,
0x33d92a3e,0x33d92a3e,0xb30e2f8b,0xb30e2f8b,0x31cbb184,0xb1cb3184,0xa7d633f1,0x27d6b3f1,0xa8b2b3ea,0xa8b2b3ea,0x31ed315f,0x31ed315f,0xb325af32,0x33252f32,0x33ceab03,0xb3ce2b03,
0xb3d9aa3e,0xb3d9aa3e,0xaf8bb30e,0xaf8bb30e,0xae7c3350,0x2e7cb350,0xb3b62c44,0x33b6ac44,0x326d30c4,0x326d30c4,0x224833fe,0x224833fe,0x320fb13a,0xb20f313a,0x33e22979,0xb3e2a979,
0x33d92a3e,0x33d92a3e,0x330eaf8b,0x330eaf8b,0x1e48b3ff,0x9e4833ff,0xb0ecb24f,0x30ec324f,0xb3ea28b2,0xb3ea28b2,0xb15f31ed,0xb15f31ed,0x2d053399,0xad05b399,0x32c23048,0xb2c2b048,
0xb3d9aa3e,0xb3d9aa3e,0x2f8b330e,0x2f8b330e,0x2dc23377,0xadc2b377,0x2fe3b2f6,0xafe332f6,0x30c4b26d,0x30c4b26d,0xb3fe2248,0xb3fe2248,0xb3faa4b5,0x33fa24b5,0x309b328a,0xb09bb28a,
0x33d92a3e,0x33d92a3e,0xb30e2f8b,0xb30e2f8b,0xb184b1cb,0x318431cb,0x33f127d6,0xb3f1a7d6,0x28b233ea,0x28b233ea,0xb1edb15f,0xb1edb15f,0x2f32b325,0xaf323325,0x2b0333ce,0xab03b3ce,
0xb3d9aa3e,0xb3d9aa3e,0xaf8bb30e,0xaf8bb30e,0x33502e7c,0xb350ae7c,0x2c4433b6,0xac44b3b6,0xb26db0c4,0xb26db0c4,0xa248b3fe,0xa248b3fe,0x313a320f,0xb13ab20f,0xa97933e2,0x2979b3e2,
0x34000000,0x34000000,0x322fb113,0x322fb113,0x33e2a979,0xb3e22979,0x313ab20f,0xb13a320f,0x3388ad64,0x3388ad64,0x301db2dd,0x301db2dd,0x32f6afe3,0xb2f62fe3,0x2dc2b377,0xadc23377,
0x34000000,0x34000000,0xb113b22f,0xb113b22f,0x32c2b048,0xb2c23048,0xb399ad05,0x33992d05,0x2ed7b33b,0x2ed7b33b,0xb3c32bc6,0xb3c32bc6,0xa7d6b3f1,0x27d633f1,0xb18431cb,0x3184b1cb,
0x34000000,0x34000000,0xb22f3113,0xb22f3113,0x309bb28a,0xb09b328a,0x24b533fa,0xa4b5b3fa,0xad64b388,0xad64b388,0x32dd301d,0x32dd301d,0xb3b6ac44,0x33b62c44,0x3350ae7c,0xb3502e7c,
0x34000000,0x34000000,0x3113322f,0x3113322f,0x2b03b3ce,0xab0333ce,0x3325af32,0xb3252f32,0xb33baed7,0xb33baed7,0xabc6b3c3,0xabc6b3c3,0xb0ec324f,0x30ecb24f,0xb3ff1e48,0x33ff9e48,
0x34000000,0x34000000,0x322fb113,0x322fb113,0xa979b3e2,0x297933e2,0xb20fb13a,0x320f313a,0xb3882d64,0xb3882d64,0xb01d32dd,0xb01d32dd,0x2fe332f6,0xafe3b2f6,0x33772dc2,0xb377adc2,
0x34000000,0x34000000,0xb113b22f,0xb113b22f,0xb048b2c2,0x304832c2,0xad053399,0x2d05b399,0xaed7333b,0xaed7333b,0x33c3abc6,0x33c3abc6,0x33f1a7d6,0xb3f127d6,0xb1cbb184,0x31cb3184,
0x34000000,0x34000000,0xb22f3113,0xb22f3113,0xb28ab09b,0x328a309b,0x33faa4b5,0xb3fa24b5,0x2d643388,0x2d643388,0xb2ddb01d,0xb2ddb01d,0x2c44b3b6,0xac4433b6,0x2e7c3350,0xae7cb350,
0x34000000,0x34000000,0x3113322f,0x3113322f,0xb3ceab03,0x33ce2b03,0xaf32b325,0x2f323325,0x333b2ed7,0x333b2ed7,0x2bc633c3,0x2bc633c3,0xb24fb0ec,0x324f30ec,0x9e48b3ff,0x1e4833ff,
0x2a3eb3d9,0x2a3eb3d9,0xaf8bb30e,0xaf8bb30e,0x1e48b3ff,0x9e4833ff,0xb0ecb24f,0x30ec324f,0xa8b2b3ea,0xa8b2b3ea,0xb1edb15f,0xb1edb15f,0xad05b399,0x2d053399,0xb2c2b048,0x32c23048,
0xaa3e33d9,0xaa3e33d9,0x330eaf8b,0x330eaf8b,0x2dc23377,0xadc2b377,0x2fe3b2f6,0xafe332f6,0x326d30c4,0x326d30c4,0xa248b3fe,0xa248b3fe,0x33fa24b5,0xb3faa4b5,0xb09bb28a,0x309b328a,
0x2a3eb3d9,0x2a3eb3d9,0x2f8b330e,0x2f8b330e,0xb184b1cb,0x318431cb,0x33f127d6,0xb3f1a7d6,0xb3ea28b2,0xb3ea28b2,0x315fb1ed,0x315fb1ed,0xaf323325,0x2f32b325,0xab03b3ce,0x2b0333ce,
0xaa3e33d9,0xaa3e33d9,0xb30e2f8b,0xb30e2f8b,0x33502e7c,0xb350ae7c,0x2c4433b6,0xac44b3b6,0x30c4b26d,0x30c4b26d,0x33fea248,0x33fea248,0xb13ab20f,0x313a320f,0x2979b3e2,0xa97933e2,
0x2a3eb3d9,0x2a3eb3d9,0xaf8bb30e,0xaf8bb30e,0xb3ff9e48,0x33ff1e48,0xb24f30ec,0x324fb0ec,0x28b233ea,0x28b233ea,0x31ed315f,0x31ed315f,0x3399ad05,0xb3992d05,0x3048b2c2,0xb04832c2,
0xaa3e33d9,0xaa3e33d9,0x330eaf8b,0x330eaf8b,0x3377adc2,0xb3772dc2,0xb2f6afe3,0x32f62fe3,0xb26db0c4,0xb26db0c4,0x224833fe,0x224833fe,0xa4b533fa,0x24b5b3fa,0x328ab09b,0xb28a309b,
0x2a3eb3d9,0x2a3eb3d9,0x2f8b330e,0x2f8b330e,0xb1cb3184,0x31cbb184,0x27d6b3f1,0xa7d633f1,0x33eaa8b2,0x33eaa8b2,0xb15f31ed,0xb15f31ed,0xb325af32,0x33252f32,0x33ceab03,0xb3ce2b03,
0xaa3e33d9,0xaa3e33d9,0xb30e2f8b,0xb30e2f8b,0x2e7cb350,0xae7c3350,0x33b6ac44,0xb3b62c44,0xb0c4326d,0xb0c4326d,0xb3fe2248,0xb3fe2248,0x320fb13a,0xb20f313a,0x33e22979,0xb3e2a979,
0x35a835a8,0x352e35a8,0x1fc60000,0x308e0000,0x35a535a7,0x2f4c33a6,0x25d423c6,0x355b342b,0x35a035a3,0xb16da7c4,0x28da27c4,0x34f735a3,0x3598359c,0xb57eb47b,0x2ac729d1,0x2d6e32e8,
0x35a535a8,0x351035a8,0x26620000,0x310e0000,0x3588359a,0x2c1332cc,0x2cc12a5e,0x35903486,0x354f356f,0xb3adae4d,0x2fd22e4d,0x3428356f,0x34fb3528,0xb5a1b54a,0x315d30a6,0xa8933002,
0x359e35a8,0x34ee35a8,0x29670000,0x318c0000,0x354c357f,0x221c31e0,0x2ff32d5d,0x35a734d6,0x34ad3505,0xb4bbb136,0x325f3136,0x32333505,0x33923443,0xb51bb5a5,0x34343371,0xb0de261b,
0x359435a8,0x34ca35a8,0x2b9a0000,0x32060000,0x34f33556,0xa92030e6,0x317c2f7e,0x359f3519,0x3385346b,0xb558b312,0x343a3312,0x2f6d346b,0x304c31fe,0xb3fab583,0x353c34cc,0xb403ad18,
0x358635a8,0x34a335a8,0x2ce40000,0x327c0000,0x347e3521,0xadd62fc1,0x32e130c6,0x35773550,0x313e3349,0xb5a2b454,0x35033454,0x28053349,0x242a2de7,0xb0ceb4e8,0x35a73576,0xb51fb1a3,
0x357535a8,0x347835a8,0x2df80000,0x32ef0000,0x33e034df,0xb07d2da2,0x341031c2,0x3531357b,0x2d4c3175,0xb596b4f5,0x358034f5,0xab0d3175,0xaea3a18d,0xa84cb3c0,0x356935a7,0xb5a2b41f,
0x356035a8,0x344b35a8,0x2f080000,0x335d0000,0x32993490,0xb1f72aea,0x349832af,0x34cf3597,0x9aaa2ed5,0xb535b565,0x35a83565,0xb06d2ed5,0xb2c4af3b,0x2d91b106,0x3489355c,0xb57cb511,
0x354935a8,0x341c35a8,0x300a0000,0x33c70000,0x312e3437,0xb35024ff,0x3507338c,0x345135a6,0xadb328fd,0xb483b59f,0x3579359f,0xb2d328fd,0xb4b7b292,0x3250ab77,0x3242349b,0xb4b2b594,
0x3c003c00,0x0,0x0,0x3c003c00,0x3c003c00,0x0,0x0,0x3c003c00,0x3c003c00,0x0,0x0,0x3c003c00,0x3c003c00,0x0,0x0,0x3c003c00,
0x39a83c00,0x39a80000,0xb9a80000,0x39a83c00,0xb9a80000,0x39a83c00,0xb9a8bc00,0xb9a80000,0xb9a8bc00,0xb9a80000,0x39a80000,0xb9a8bc00,0x39a80000,0xb9a8bc00,0x39a83c00,0x39a80000,
0x3c00,0x3c000000,0xbc000000,0x3c00,0xbc00,0xbc000000,0x3c000000,0xbc00,0x3c00,0x3c000000,0xbc000000,0x3c00,0xbc00,0xbc000000,0x3c000000,0xbc00,
0xb9a83c00,0x39a80000,0xb9a80000,0xb9a83c00,0x39a80000,0x39a8bc00,0xb9a83c00,0x39a80000,0x39a8bc00,0xb9a80000,0x39a80000,0x39a8bc00,0xb9a80000,0xb9a83c00,0x39a8bc00,0xb9a80000,
0xbc003c00,0x0,0x0,0xbc003c00,0xbc003c00,0x0,0x0,0xbc003c00,0xbc003c00,0x0,0x0,0xbc003c00,0xbc003c00,0x0,0x0,0xbc003c00,
0xb9a83c00,0xb9a80000,0x39a80000,0xb9a83c00,0x39a80000,0xb9a83c00,0x39a8bc00,0x39a80000,0x39a8bc00,0x39a80000,0xb9a80000,0x39a8bc00,0xb9a80000,0x39a8bc00,0xb9a83c00,0xb9a80000,
0x3c00,0xbc000000,0x3c000000,0x3c00,0xbc00,0x3c000000,0xbc000000,0xbc00,0x3c00,0xbc000000,0x3c000000,0x3c00,0xbc00,0x3c000000,0xbc000000,0xbc00,
0x39a83c00,0xb9a80000,0x39a80000,0x39a83c00,0xb9a80000,0xb9a8bc00,0x39a83c00,0xb9a80000,0xb9a8bc00,0x39a80000,0xb9a80000,0xb9a8bc00,0x39a80000,0x39a83c00,0xb9a8bc00,0x39a80000,
0x3c003c00,0x0,0x0,0x3c003c00,0x3c003c00,0x0,0x0,0x3c003c00,0x3c003c00,0x0,0x0,0x3c003c00,0x3c003c00,0x0,0x0,0x3c003c00,
0x39a83c00,0x39a80000,0xb9a80000,0x39a83c00,0xb9a80000,0x39a83c00,0xb9a8bc00,0xb9a80000,0xb9a8bc00,0xb9a80000,0x39a80000,0xb9a8bc00,0x39a80000,0xb9a8bc00,0x39a83c00,0x39a80000,
0x3c00,0x3c000000,0xbc000000,0x3c00,0xbc00,0xbc000000,0x3c000000,0xbc00,0x3c00,0x3c000000,0xbc000000,0x3c00,0xbc00,0xbc000000,0x3c000000,0xbc00,
0xb9a83c00,0x39a80000,0xb9a80000,0xb9a83c00,0x39a80000,0x39a8bc00,0xb9a83c00,0x39a80000,0x39a8bc00,0xb9a80000,0x39a80000,0x39a8bc00,0xb9a80000,0xb9a83c00,0x39a8bc00,0xb9a80000,
0xbc003c00,0x0,0x0,0xbc003c00,0xbc003c00,0x0,0x0,0xbc003c00,0xbc003c00,0x0,0x0,0xbc003c00,0xbc003c00,0x0,0x0,0xbc003c00,
0xb9a83c00,0xb9a80000,0x39a80000,0xb9a83c00,0x39a80000,0xb9a83c00,0x39a8bc00,0x39a80000,0x39a8bc00,0x39a80000,0xb9a80000,0x39a8bc00,0xb9a80000,0x39a8bc00,0xb9a83c00,0xb9a80000,
0x3c00,0xbc000000,0x3c000000,0x3c00,0xbc00,0x3c000000,0xbc000000,0xbc00,0x3c00,0xbc000000,0x3c000000,0x3c00,0xbc00,0x3c000000,0xbc000000,0xbc00,
0x39a83c00,0xb9a80000,0x39a80000,0x39a83c00,0xb9a80000,0xb9a8bc00,0x39a83c00,0xb9a80000,0xb9a8bc00,0x39a80000,0xb9a80000,0xb9a8bc00,0x39a80000,0x39a83c00,0xb9a8bc00,0x39a80000,
0x35a835a8,0x35a835a8,0x0,0x0,0x35a835a8,0x35a835a8,0x0,0x0,0x35a835a8,0x35a835a8,0x0,0x0,0x35a835a8,0x35a835a8,0x0,0x0,
0x35a535a8,0x3510352e,0x26621fc6,0x310e308e,0x3594359e,0x34ca34ee,0x2b9a2967,0x3206318c,0x35753586,0x347834a3,0x2df82ce4,0x32ef327c,0x35493560,0x341c344b,0x300a2f08,0x33c7335d,
0x359a35a7,0x32cc33a6,0x2a5e23c6,0x3486342b,0x3556357f,0x30e631e0,0x2f7e2d5d,0x351934d6,0x34df3521,0x2da22fc1,0x31c230c6,0x357b3550,0x34373490,0x24ff2aea,0x338c32af,0x35a63597,
0x358835a5,0x2c132f4c,0x2cc125d4,0x3590355b,0x34f3354c,0xa920221c,0x317c2ff3,0x359f35a7,0x33e0347e,0xb07dadd6,0x341032e1,0x35313577,0x312e3299,0xb350b1f7,0x35073498,0x345134cf,
0x356f35a3,0xae4da7c4,0x2e4d27c4,0x356f35a3,0x346b3505,0xb312b136,0x33123136,0x346b3505,0x31753349,0xb4f5b454,0x34f53454,0x31753349,0x28fd2ed5,0xb59fb565,0x359f3565,0x28fd2ed5,
0x354f35a0,0xb3adb16d,0x2fd228da,0x342834f7,0x338534ad,0xb558b4bb,0x343a325f,0x2f6d3233,0x2d4c313e,0xb596b5a2,0x35803503,0xab0d2805,0xadb39aaa,0xb483b535,0x357935a8,0xb2d3b06d,
0x3528359c,0xb54ab47b,0x30a629d1,0x300232e8,0x31fe3443,0xb583b5a5,0x34cc3371,0xad18261b,0xa18d2de7,0xb3c0b4e8,0x35a73576,0xb41fb1a3,0xb292af3b,0xab77b106,0x349b355c,0xb594b511,
0x34fb3598,0xb5a1b57e,0x315d2ac7,0xa8932d6e,0x304c3392,0xb3fab51b,0x353c3434,0xb403b0de,0xaea3242a,0xa84cb0ce,0x356935a7,0xb5a2b51f,0xb4b7b2c4,0x32502d91,0x32423489,0xb4b2b57c,
0x34003400,0x34003400,0x0,0x0,0x34003400,0x34003400,0x0,0x0,0x34003400,0x34003400,0x0,0x0,0x34003400,0x34003400,0x0,0x0,
0x0,0x0,0x34003400,0x34003400,0x0,0x0,0x34003400,0x34003400,0x0,0x0,0x34003400,0x34003400,0x0,0x0,0x34003400,0x34003400,
0x32c233e2,0xb2c2b3e2,0xb048a979,0x30482979,0x2b03309b,0xab03b09b,0xb3ceb28a,0x33ce328a,0xb048a979,0x30482979,0xb2c2b3e2,0x32c233e2,0xb3ceb28a,0x33ce328a,0xab03b09b,0x2b03309b,
0x30482979,0xb048a979,0x32c233e2,0xb2c2b3e2,0x33ce328a,0xb3ceb28a,0x2b03309b,0xab03b09b,0x32c233e2,0xb2c2b3e2,0xb048a979,0x30482979,0x2b03309b,0xab03b09b,0xb3ceb28a,0x33ce328a,
0x2ed73388,0x2ed73388,0xb33bad64,0xb33bad64,0xb33bad64,0xb33bad64,0xaed7b388,0xaed7b388,0xaed7b388,0xaed7b388,0x333b2d64,0x333b2d64,0x333b2d64,0x333b2d64,0x2ed73388,0x2ed73388,
0x333b2d64,0x333b2d64,0x2ed73388,0x2ed73388,0x2ed73388,0x2ed73388,0xb33bad64,0xb33bad64,0xb33bad64,0xb33bad64,0xaed7b388,0xaed7b388,0xaed7b388,0xaed7b388,0x333b2d64,0x333b2d64,
0xa7d632f6,0x27d6b2f6,0xb3f1afe3,0x33f12fe3,0xb0ecb3b6,0x30ec33b6,0x324fac44,0xb24f2c44,0x33f12fe3,0xb3f1afe3,0xa7d632f6,0x27d6b2f6,0xb24f2c44,0x324fac44,0xb0ecb3b6,0x30ec33b6,
0x33f12fe3,0xb3f1afe3,0xa7d632f6,0x27d6b2f6,0xb24f2c44,0x324fac44,0xb0ecb3b6,0x30ec33b6,0x27d6b2f6,0xa7d632f6,0x33f12fe3,0xb3f1afe3,0x30ec33b6,0xb0ecb3b6,0xb24f2c44,0x324fac44,
0xb113322f,0xb113322f,0xb22fb113,0xb22fb113,0x3113b22f,0x3113b22f,0x322f3113,0x322f3113,0xb113322f,0xb113322f,0xb22fb113,0xb22fb113,0x3113b22f,0x3113b22f,0x322f3113,0x322f3113,
0x322f3113,0x322f3113,0xb113322f,0xb113322f,0xb22fb113,0xb22fb113,0x3113b22f,0x3113b22f,0x322f3113,0x322f3113,0xb113322f,0xb113322f,0xb22fb113,0xb22fb113,0x3113b22f,0x3113b22f,
0xb399313a,0x3399b13a,0xad05b20f,0x2d05320f,0x332524b5,0xb325a4b5,0xaf3233fa,0x2f32b3fa,0xad05b20f,0x2d05320f,0x3399b13a,0xb399313a,0xaf3233fa,0x2f32b3fa,0xb325a4b5,0x332524b5,
0x2d05320f,0xad05b20f,0xb399313a,0x3399b13a,0x2f32b3fa,0xaf3233fa,0x332524b5,0xb325a4b5,0xb399313a,0x3399b13a,0xad05b20f,0x2d05320f,0x332524b5,0xb325a4b5,0xaf3233fa,0x2f32b3fa,
0xb3c3301d,0xb3c3301d,0x2bc6b2dd,0x2bc6b2dd,0xabc632dd,0xabc632dd,0xb3c3301d,0xb3c3301d,0x33c3b01d,0x33c3b01d,0xabc632dd,0xabc632dd,0x2bc6b2dd,0x2bc6b2dd,0x33c3b01d,0x33c3b01d,
0xabc632dd,0xabc632dd,0xb3c3301d,0xb3c3301d,0x33c3b01d,0x33c3b01d,0xabc632dd,0xabc632dd,0x2bc6b2dd,0x2bc6b2dd,0x33c3b01d,0x33c3b01d,0xb3c3301d,0xb3c3301d,0x2bc6b2dd,0x2bc6b2dd,
0xb1842dc2,0x3184adc2,0x31cbb377,0xb1cb3377,0xb3ff3350,0x33ffb350,0x1e48ae7c,0x9e482e7c,0xb1cb3377,0x31cbb377,0xb1842dc2,0x3184adc2,0x9e482e7c,0x1e48ae7c,0xb3ff3350,0x33ffb350,
0xb1cb3377,0x31cbb377,0xb1842dc2,0x3184adc2,0x9e482e7c,0x1e48ae7c,0xb3ff3350,0x33ffb350,0x3184adc2,0xb1842dc2,0xb1cb3377,0x31cbb377,0x33ffb350,0xb3ff3350,0x9e482e7c,0x1e48ae7c,
0xaa3e2a3e,0xaa3e2a3e,0x33d9b3d9,0x33d9b3d9,0xaa3e2a3e,0xaa3e2a3e,0x33d9b3d9,0x33d9b3d9,0xaa3e2a3e,0xaa3e2a3e,0x33d9b3d9,0x33d9b3d9,0xaa3e2a3e,0xaa3e2a3e,0x33d9b3d9,0x33d9b3d9,
0xb3d933d9,0xb3d933d9,0xaa3e2a3e,0xaa3e2a3e,0xb3d933d9,0xb3d933d9,0xaa3e2a3e,0xaa3e2a3e,0xb3d933d9,0xb3d933d9,0xaa3e2a3e,0xaa3e2a3e,0xb3d933d9,0xb3d933d9,0xaa3e2a3e,0xaa3e2a3e,
0x2dc21e48,0xadc29e48,0x3377b3ff,0xb37733ff,0x3350b184,0xb3503184,0x2e7cb1cb,0xae7c31cb,0x3377b3ff,0xb37733ff,0xadc29e48,0x2dc21e48,0x2e7cb1cb,0xae7c31cb,0xb3503184,0x3350b184,
0xb37733ff,0x3377b3ff,0x2dc21e48,0xadc29e48,0xae7c31cb,0x2e7cb1cb,0x3350b184,0xb3503184,0x2dc21e48,0xadc29e48,0x3377b3ff,0xb37733ff,0x3350b184,0xb3503184,0x2e7cb1cb,0xae7c31cb,
0x326da8b2,0x326da8b2,0x30c4b3ea,0x30c4b3ea,0x30c4b3ea,0x30c4b3ea,0xb26d28b2,0xb26d28b2,0xb26d28b2,0xb26d28b2,0xb0c433ea,0xb0c433ea,0xb0c433ea,0xb0c433ea,0x326da8b2,0x326da8b2,
0xb0c433ea,0xb0c433ea,0x326da8b2,0x326da8b2,0x326da8b2,0x326da8b2,0x30c4b3ea,0x30c4b3ea,0x30c4b3ea,0x30c4b3ea,0xb26d28b2,0xb26d28b2,0xb26d28b2,0xb26d28b2,0xb0c433ea,0xb0c433ea,
0x33faad05,0xb3fa2d05,0x24b5b399,0xa4b53399,0xb13aaf32,0x313a2f32,0xb20f3325,0x320fb325,0xa4b53399,0x24b5b399,0x33faad05,0xb3fa2d05,0x320fb325,0xb20f3325,0xb13aaf32,0x313a2f32,
0xa4b53399,0x24b5b399,0x33faad05,0xb3fa2d05,0x320fb325,0xb20f3325,0xb13aaf32,0x313a2f32,0xb3fa2d05,0x33faad05,0xa4b53399,0x24b5b399,0x313a2f32,0xb13aaf32,0x320fb325,0xb20f3325,
0x330eaf8b,0x330eaf8b,0xaf8bb30e,0xaf8bb30e,0xb30e2f8b,0xb30e2f8b,0x2f8b330e,0x2f8b330e,0x330eaf8b,0x330eaf8b,0xaf8bb30e,0xaf8bb30e,0xb30e2f8b,0xb30e2f8b,0x2f8b330e,0x2f8b330e,
0x2f8b330e,0x2f8b330e,0x330eaf8b,0x330eaf8b,0xaf8bb30e,0xaf8bb30e,0xb30e2f8b,0xb30e2f8b,0x2f8b330e,0x2f8b330e,0x330eaf8b,0x330eaf8b,0xaf8bb30e,0xaf8bb30e,0xb30e2f8b,0xb30e2f8b,
0x2fe3b0ec,0xafe330ec,0xb2f6b24f,0x32f6324f,0x2c4433f1,0xac44b3f1,0x33b627d6,0xb3b6a7d6,0xb2f6b24f,0x32f6324f,0xafe330ec,0x2fe3b0ec,0x33b627d6,0xb3b6a7d6,0xac44b3f1,0x2c4433f1,
0x32f6324f,0xb2f6b24f,0x2fe3b0ec,0xafe330ec,0xb3b6a7d6,0x33b627d6,0x2c4433f1,0xac44b3f1,0x2fe3b0ec,0xafe330ec,0xb2f6b24f,0x32f6324f,0x2c4433f1,0xac44b3f1,0x33b627d6,0xb3b6a7d6,
0xa248b1ed,0xa248b1ed,0xb3feb15f,0xb3feb15f,0x33fe315f,0x33fe315f,0xa248b1ed,0xa248b1ed,0x224831ed,0x224831ed,0x33fe315f,0x33fe315f,0xb3feb15f,0xb3feb15f,0x224831ed,0x224831ed,
0x33fe315f,0x33fe315f,0xa248b1ed,0xa248b1ed,0x224831ed,0x224831ed,0x33fe315f,0x33fe315f,0xb3feb15f,0xb3feb15f,0x224831ed,0x224831ed,0xa248b1ed,0xa248b1ed,0xb3feb15f,0xb3feb15f,
0xb09bb2c2,0x309b32c2,0xb28ab048,0x328a3048,0x2979ab03,0xa9792b03,0xb3e2b3ce,0x33e233ce,0x328a3048,0xb28ab048,0xb09bb2c2,0x309b32c2,0x33e233ce,0xb3e2b3ce,0x2979ab03,0xa9792b03,
0x328a3048,0xb28ab048,0xb09bb2c2,0x309b32c2,0x33e233ce,0xb3e2b3ce,0x2979ab03,0xa9792b03,0x309b32c2,0xb09bb2c2,0x328a3048,0xb28ab048,0xa9792b03,0x2979ab03,0x33e233ce,0xb3e2b3ce,
0x3400,0x3400,0x31a831a8,0x31a831a8,0x2a3e33d9,0xaa3eb3d9,0x32a73072,0xb2a7b072,0x2e1f3364,0x2e1f3364,0x33642e1f,0x33642e1f,0x307232a7,0xb072b2a7,0x33d92a3e,0xb3d9aa3e,
0x3400,0x3400,0x31a8b1a8,0x31a8b1a8,0x307232a7,0xb072b2a7,0x2a3eb3d9,0xaa3e33d9,0x33642e1f,0x33642e1f,0xae1fb364,0xae1fb364,0x33d9aa3e,0xb3d92a3e,0xb2a7b072,0x32a73072,
0x3400,0x3400,0xb1a8b1a8,0xb1a8b1a8,0x32a73072,0xb2a7b072,0xb3d92a3e,0x33d9aa3e,0x3364ae1f,0x3364ae1f,0xae1f3364,0xae1f3364,0x2a3eb3d9,0xaa3e33d9,0x307232a7,0xb072b2a7,
0x3400,0x3400,0xb1a831a8,0xb1a831a8,0x33d92a3e,0xb3d9aa3e,0x307232a7,0xb072b2a7,0x2e1fb364,0x2e1fb364,0x3364ae1f,0x3364ae1f,0xb2a7b072,0x32a73072,0xaa3eb3d9,0x2a3e33d9,
0x3400,0x3400,0x31a831a8,0x31a831a8,0x33d9aa3e,0xb3d92a3e,0x3072b2a7,0xb07232a7,0xae1fb364,0xae1fb364,0xb364ae1f,0xb364ae1f,0xb2a73072,0x32a7b072,0xaa3e33d9,0x2a3eb3d9,
0x3400,0x3400,0x31a8b1a8,0x31a8b1a8,0x32a7b072,0xb2a73072,0xb3d9aa3e,0x33d92a3e,0xb364ae1f,0xb364ae1f,0x2e1f3364,0x2e1f3364,0x2a3e33d9,0xaa3eb3d9,0x3072b2a7,0xb07232a7,
0x3400,0x3400,0xb1a8b1a8,0xb1a8b1a8,0x3072b2a7,0xb07232a7,0x2a3e33d9,0xaa3eb3d9,0xb3642e1f,0xb3642e1f,0x2e1fb364,0x2e1fb364,0x33d92a3e,0xb3d9aa3e,0xb2a73072,0x32a7b072,
0x3400,0x3400,0xb1a831a8,0xb1a831a8,0x2a3eb3d9,0xaa3e33d9,0x32a7b072,0xb2a73072,0xae1f3364,0xae1f3364,0xb3642e1f,0xb3642e1f,0x3072b2a7,0xb07232a7,0x33d9aa3e,0xb3d92a3e,
0x34000000,0x34000000,0x31a8b1a8,0x31a8b1a8,0x33d9aa3e,0xb3d92a3e,0x3072b2a7,0xb07232a7,0x3364ae1f,0x3364ae1f,0x2e1fb364,0x2e1fb364,0x32a7b072,0xb2a73072,0x2a3eb3d9,0xaa3e33d9,
0xb4000000,0xb4000000,0x31a831a8,0x31a831a8,0xb2a73072,0x32a7b072,0x33d92a3e,0xb3d9aa3e,0xae1f3364,0xae1f3364,0x3364ae1f,0x3364ae1f,0x2a3e33d9,0xaa3eb3d9,0x3072b2a7,0xb07232a7,
0x34000000,0x34000000,0xb1a831a8,0xb1a831a8,0x3072b2a7,0xb07232a7,0x2a3e33d9,0xaa3eb3d9,0xae1fb364,0xae1fb364,0x33642e1f,0x33642e1f,0xb3d9aa3e,0x33d92a3e,0x32a7b072,0xb2a73072,
0xb4000000,0xb4000000,0xb1a8b1a8,0xb1a8b1a8,0xaa3e33d9,0x2a3eb3d9,0xb2a73072,0x32a7b072,0x33642e1f,0x33642e1f,0x2e1f3364,0x2e1f3364,0x3072b2a7,0xb07232a7,0x33d9aa3e,0xb3d92a3e,
0x34000000,0x34000000,0x31a8b1a8,0x31a8b1a8,0xaa3eb3d9,0x2a3e33d9,0xb2a7b072,0x32a73072,0xb3642e1f,0xb3642e1f,0xae1f3364,0xae1f3364,0x307232a7,0xb072b2a7,0x33d92a3e,0xb3d9aa3e,
0xb4000000,0xb4000000,0x31a831a8,0x31a831a8,0x307232a7,0xb072b2a7,0x2a3eb3d9,0xaa3e33d9,0x2e1fb364,0x2e1fb364,0xb3642e1f,0xb3642e1f,0xb3d92a3e,0x33d9aa3e,0x32a73072,0xb2a7b072,
0x34000000,0x34000000,0xb1a831a8,0xb1a831a8,0xb2a7b072,0x32a73072,0x33d9aa3e,0xb3d92a3e,0x2e1f3364,0x2e1f3364,0xb364ae1f,0xb364ae1f,0x2a3eb3d9,0xaa3e33d9,0x307232a7,0xb072b2a7,
0xb4000000,0xb4000000,0xb1a8b1a8,0xb1a8b1a8,0x33d92a3e,0xb3d9aa3e,0x307232a7,0xb072b2a7,0xb364ae1f,0xb364ae1f,0xae1fb364,0xae1fb364,0x32a73072,0xb2a7b072,0x2a3e33d9,0xaa3eb3d9,
0x34000000,0x34000000,0x31a8b1a8,0x31a8b1a8,0x33d9aa3e,0xb3d92a3e,0x3072b2a7,0xb07232a7,0x3364ae1f,0x3364ae1f,0x2e1fb364,0x2e1fb364,0x32a7b072,0xb2a73072,0x2a3eb3d9,0xaa3e33d9,
0x34000000,0x34000000,0xb1a8b1a8,0xb1a8b1a8,0x32a7b072,0xb2a73072,0xb3d9aa3e,0x33d92a3e,0x2e1fb364,0x2e1fb364,0xb3642e1f,0xb3642e1f,0xaa3eb3d9,0x2a3e33d9,0xb07232a7,0x3072b2a7,
0x34000000,0x34000000,0xb1a831a8,0xb1a831a8,0x3072b2a7,0xb07232a7,0x2a3e33d9,0xaa3eb3d9,0xae1fb364,0xae1fb364,0x33642e1f,0x33642e1f,0xb3d9aa3e,0x33d92a3e,0x32a7b072,0xb2a73072,
0x34000000,0x34000000,0x31a831a8,0x31a831a8,0x2a3eb3d9,0xaa3e33d9,0x32a7b072,0xb2a73072,0xb364ae1f,0xb364ae1f,0xae1fb364,0xae1fb364,0xb07232a7,0x3072b2a7,0xb3d92a3e,0x33d9aa3e,
0x34000000,0x34000000,0x31a8b1a8,0x31a8b1a8,0xaa3eb3d9,0x2a3e33d9,0xb2a7b072,0x32a73072,0xb3642e1f,0xb3642e1f,0xae1f3364,0xae1f3364,0x307232a7,0xb072b2a7,0x33d92a3e,0xb3d9aa3e,
0x34000000,0x34000000,0xb1a8b1a8,0xb1a8b1a8,0xb072b2a7,0x307232a7,0xaa3e33d9,0x2a3eb3d9,0xae1f3364,0xae1f3364,0x3364ae1f,0x3364ae1f,0x33d9aa3e,0xb3d92a3e,0xb2a7b072,0x32a73072,
0x34000000,0x34000000,0xb1a831a8,0xb1a831a8,0xb2a7b072,0x32a73072,0x33d9aa3e,0xb3d92a3e,0x2e1f3364,0x2e1f3364,0xb364ae1f,0xb364ae1f,0x2a3eb3d9,0xaa3e33d9,0x307232a7,0xb072b2a7,
0x34000000,0x34000000,0x31a831a8,0x31a831a8,0xb3d9aa3e,0x33d92a3e,0xb072b2a7,0x307232a7,0x33642e1f,0x33642e1f,0x2e1f3364,0x2e1f3364,0xb2a7b072,0x32a73072,0xaa3eb3d9,0x2a3e33d9,
0xb400,0xb400,0xb1a8b1a8,0xb1a8b1a8,0xaa3eb3d9,0x2a3e33d9,0xb2a7b072,0x32a73072,0xae1fb364,0xae1fb364,0xb364ae1f,0xb364ae1f,0xb072b2a7,0x307232a7,0xb3d9aa3e,0x33d92a3e,
0x3400,0x3400,0x31a8b1a8,0x31a8b1a8,0x307232a7,0xb072b2a7,0x2a3eb3d9,0xaa3e33d9,0x33642e1f,0x33642e1f,0xae1fb364,0xae1fb364,0x33d9aa3e,0xb3d92a3e,0xb2a7b072,0x32a73072,
0xb400,0xb400,0x31a831a8,0x31a831a8,0xb2a7b072,0x32a73072,0x33d9aa3e,0xb3d92a3e,0xb3642e1f,0xb3642e1f,0x2e1fb364,0x2e1fb364,0xaa3e33d9,0x2a3eb3d9,0xb072b2a7,0x307232a7,
0x3400,0x3400,0xb1a831a8,0xb1a831a8,0x33d92a3e,0xb3d9aa3e,0x307232a7,0xb072b2a7,0x2e1fb364,0x2e1fb364,0x3364ae1f,0x3364ae1f,0xb2a7b072,0x32a73072,0xaa3eb3d9,0x2a3e33d9,
0xb400,0xb400,0xb1a8b1a8,0xb1a8b1a8,0xb3d92a3e,0x33d9aa3e,0xb07232a7,0x3072b2a7,0x2e1f3364,0x2e1f3364,0x33642e1f,0x33642e1f,0x32a7b072,0xb2a73072,0x2a3eb3d9,0xaa3e33d9,
0x3400,0x3400,0x31a8b1a8,0x31a8b1a8,0x32a7b072,0xb2a73072,0xb3d9aa3e,0x33d92a3e,0xb364ae1f,0xb364ae1f,0x2e1f3364,0x2e1f3364,0x2a3e33d9,0xaa3eb3d9,0x3072b2a7,0xb07232a7,
0xb400,0xb400,0x31a831a8,0x31a831a8,0xb07232a7,0x3072b2a7,0xaa3eb3d9,0x2a3e33d9,0x3364ae1f,0x3364ae1f,0xae1f3364,0xae1f3364,0xb3d9aa3e,0x33d92a3e,0x32a7b072,0xb2a73072,
0x3400,0x3400,0xb1a831a8,0xb1a831a8,0x2a3eb3d9,0xaa3e33d9,0x32a7b072,0xb2a73072,0xae1f3364,0xae1f3364,0xb3642e1f,0xb3642e1f,0x3072b2a7,0xb07232a7,0x33d9aa3e,0xb3d92a3e,
0x35a835a8,0x352c35a8,0x20710000,0x30960000,0x35a435a6,0x2f193399,0x26a92471,0x355f3431,0x359d35a1,0xb194a870,0x298a2870,0x34ec35a1,0x35933598,0xb585b48b,0x2bbd2aa4,0x2cf532bd,
0x35a435a8,0x350e35a8,0x26a90000,0x31160000,0x35853598,0x2bbd32bd,0x2cf52aa4,0x3593348b,0x3547356a,0xb3cdae92,0x30122e92,0x3419356a,0x34ec351d,0xb59db554,0x319430d6,0xa98a2f9f,
0x359d35a8,0x34ec35a8,0x298a0000,0x31940000,0x3547357d,0x207131d1,0x30122d7f,0x35a834da,0x34a034fd,0xb4c7b155,0x32843155,0x320e34fd,0x33643431,0xb50eb5a6,0x34493399,0xb1162471,
0x359335a8,0x34c735a8,0x2bbd0000,0x320e0000,0x34ec3554,0xa98a30d6,0x31942f9f,0x359d351d,0x3364345f,0xb55fb32d,0x3449332d,0x2f19345f,0x301231d1,0xb3cdb57d,0x354734da,0xb419ad7f,
0x358535a8,0x34a035a8,0x2cf50000,0x32840000,0x3476351d,0xae092f9f,0x32f630d6,0x35743554,0x3116332d,0xb5a4b45f,0x350e345f,0x26a9332d,0x20712d7f,0xb096b4da,0x35a8357d,0xb52cb1d1,
0x357435a8,0x347635a8,0x2e090000,0x32f60000,0x33cd34da,0xb0962d7f,0x341931d1,0x352c357d,0x2cf53155,0xb593b4fd,0x358534fd,0xabbd3155,0xaf19a471,0xa6a9b399,0x355f35a6,0xb5a4b431,
0x355f35a8,0x344935a8,0x2f190000,0x33640000,0x3284348b,0xb20e2aa4,0x34a032bd,0x34c73598,0xa0712e92,0xb52cb56a,0x35a8356a,0xb0962e92,0xb2f6af9f,0x2e09b0d6,0x34763554,0xb574b51d,
0x354735a8,0x341935a8,0x30120000,0x33cd0000,0x31163431,0xb3642471,0x350e3399,0x344935a6,0xae092870,0xb476b5a1,0x357435a1,0xb2f62870,0xb4c7b2bd,0x3284aaa4,0x320e348b,0xb4a0b598,
0x3c003c00,0x0,0x0,0x3c003c00,0x3c003c00,0x0,0x0,0x3c003c00,0x3c003c00,0x0,0x0,0x3c003c00,0x3c003c00,0x0,0x0,0x3c003c00,
0x39a83c00,0x39a80000,0xb9a80000,0x39a83c00,0xb9a80000,0x39a83c00,0xb9a8bc00,0xb9a80000,0xb9a8bc00,0xb9a80000,0x39a80000,0xb9a8bc00,0x39a80000,0xb9a8bc00,0x39a83c00,0x39a80000,
0x3c00,0x3c000000,0xbc000000,0x3c00,0xbc00,0xbc000000,0x3c000000,0xbc00,0x3c00,0x3c000000,0xbc000000,0x3c00,0xbc00,0xbc000000,0x3c000000,0xbc00,
0xb9a83c00,0x39a80000,0xb9a80000,0xb9a83c00,0x39a80000,0x39a8bc00,0xb9a83c00,0x39a80000,0x39a8bc00,0xb9a80000,0x39a80000,0x39a8bc00,0xb9a80000,0xb9a83c00,0x39a8bc00,0xb9a80000,
0xbc003c00,0x0,0x0,0xbc003c00,0xbc003c00,0x0,0x0,0xbc003c00,0xbc003c00,0x0,0x0,0xbc003c00,0xbc003c00,0x0,0x0,0xbc003c00,
0xb9a83c00,0xb9a80000,0x39a80000,0xb9a83c00,0x39a80000,0xb9a83c00,0x39a8bc00,0x39a80000,0x39a8bc00,0x39a80000,0xb9a80000,0x39a8bc00,0xb9a80000,0x39a8bc00,0xb9a83c00,0xb9a80000,
0x3c00,0xbc000000,0x3c000000,0x3c00,0xbc00,0x3c000000,0xbc000000,0xbc00,0x3c00,0xbc000000,0x3c000000,0x3c00,0xbc00,0x3c000000,0xbc000000,0xbc00,
0x39a83c00,0xb9a80000,0x39a80000,0x39a83c00,0xb9a80000,0xb9a8bc00,0x39a83c00,0xb9a80000,0xb9a8bc00,0x39a80000,0xb9a80000,0xb9a8bc00,0x39a80000,0x39a83c00,0xb9a8bc00,0x39a80000,
0x3c003c00,0x0,0x0,0x3c003c00,0x3c003c00,0x0,0x0,0x3c003c00,0x3c003c00,0x0,0x0,0x3c003c00,0x3c003c00,0x0,0x0,0x3c003c00,
0x39a83c00,0x39a80000,0xb9a80000,0x39a83c00,0xb9a80000,0x39a83c00,0xb9a8bc00,0xb9a80000,0xb9a8bc00,0xb9a80000,0x39a80000,0xb9a8bc00,0x39a80000,0xb9a8bc00,0x39a83c00,0x39a80000,
0x3c00,0x3c000000,0xbc000000,0x3c00,0xbc00,0xbc000000,0x3c000000,0xbc00,0x3c00,0x3c000000,0xbc000000,0x3c00,0xbc00,0xbc000000,0x3c000000,0xbc00,
0xb9a83c00,0x39a80000,0xb9a80000,0xb9a83c00,0x39a80000,0x39a8bc00,0xb9a83c00,0x39a80000,0x39a8bc00,0xb9a80000,0x39a80000,0x39a8bc00,0xb9a80000,0xb9a83c00,0x39a8bc00,0xb9a80000,
0xbc003c00,0x0,0x0,0xbc003c00,0xbc003c00,0x0,0x0,0xbc003c00,0xbc003c00,0x0,0x0,0xbc003c00,0xbc003c00,0x0,0x0,0xbc003c00,
0xb9a83c00,0xb9a80000,0x39a80000,0xb9a83c00,0x39a80000,0xb9a83c00,0x39a8bc00,0x39a80000,0x39a8bc00,0x39a80000,0xb9a80000,0x39a8bc00,0xb9a80000,0x39a8bc00,0xb9a83c00,0xb9a80000,
0x3c00,0xbc000000,0x3c000000,0x3c00,0xbc00,0x3c000000,0xbc000000,0xbc00,0x3c00,0xbc000000,0x3c000000,0x3c00,0xbc00,0x3c000000,0xbc000000,0xbc00,
0x39a83c00,0xb9a80000,0x39a80000,0x39a83c00,0xb9a80000,0xb9a8bc00,0x39a83c00,0xb9a80000,0xb9a8bc00,0x39a80000,0xb9a80000,0xb9a8bc00,0x39a80000,0x39a83c00,0xb9a8bc00,0x39a80000,
0x2da82da8,0x2da82da8,0x0,0x0,0x2da82da8,0x2da82da8,0x0,0x0,0x2da82da8,0x2da82da8,0x0,0x0,0x2da82da8,0x2da82da8,0x0,0x0,
0x2da42da8,0x2d0e2d2c,0x1ea91871,0x29162896,0x2d932d9d,0x2cc72cec,0x23bd218a,0x2a0e2994,0x2d742d85,0x2c762ca0,0x260924f5,0x2af62a84,0x2d472d5f,0x2c192c49,0x28122719,0x2bcd2b64,
0x2d982da6,0x2abd2b99,0x22a41c71,0x2c8b2c31,0x2d542d7d,0x28d629d1,0x279f257f,0x2d1d2cda,0x2cda2d1d,0x257f279f,0x29d128d6,0x2d7d2d54,0x2c312c8b,0x1c7122a4,0x2b992abd,0x2da62d98,
0x2d852da4,0x23bd2719,0x24f51ea9,0x2d932d5f,0x2cec2d47,0xa18a1871,0x29942812,0x2d9d2da8,0x2bcd2c76,0xa896a609,0x2c192af6,0x2d2c2d74,0x29162a84,0xab64aa0e,0x2d0e2ca0,0x2c492cc7,
0x2d6a2da1,0xa692a070,0x26922070,0x2d6a2da1,0x2c5f2cfd,0xab2da955,0x2b2d2955,0x2c5f2cfd,0x29552b2d,0xacfdac5f,0x2cfd2c5f,0x29552b2d,0x20702692,0xada1ad6a,0x2da12d6a,0x20702692,
0x2d472d9d,0xabcda994,0x2812218a,0x2c192cec,0x2b642ca0,0xad5facc7,0x2c492a84,0x27192a0e,0x24f52916,0xad93ada4,0x2d852d0e,0xa3bd1ea9,0xa6099871,0xac76ad2c,0x2d742da8,0xaaf6a896,
0x2d1d2d98,0xad54ac8b,0x28d622a4,0x279f2abd,0x29d12c31,0xad7dada6,0x2cda2b99,0xa57f1c71,0x9c71257f,0xab99acda,0x2da62d7d,0xac31a9d1,0xaabda79f,0xa2a4a8d6,0x2c8b2d54,0xad98ad1d,
0x2cec2d93,0xad9dad85,0x299423bd,0xa18a24f5,0x28122b64,0xabcdad0e,0x2d472c49,0xac19a916,0xa7191871,0x9ea9a896,0x2d5f2da8,0xada4ad2c,0xacc7aaf6,0x2a842609,0x2a0e2c76,0xaca0ad74,
0x34003400,0x34003400,0x0,0x0,0x34003400,0x34003400,0x0,0x0,0x34003400,0x34003400,0x0,0x0,0x34003400,0x34003400,0x0,0x0,
0x0,0x0,0x34003400,0x34003400,0x0,0x0,0x34003400,0x34003400,0x0,0x0,0x34003400,0x34003400,0x0,0x0,0x34003400,0x34003400,
0x32a733d9,0xb2a7b3d9,0xb072aa3e,0x30722a3e,0x2a3e3072,0xaa3eb072,0xb3d9b2a7,0x33d932a7,0xb072aa3e,0x30722a3e,0xb2a7b3d9,0x32a733d9,0xb3d9b2a7,0x33d932a7,0xaa3eb072,0x2a3e3072,
0x30722a3e,0xb072aa3e,0x32a733d9,0xb2a7b3d9,0x33d932a7,0xb3d9b2a7,0x2a3e3072,0xaa3eb072,0x32a733d9,0xb2a7b3d9,0xb072aa3e,0x30722a3e,0x2a3e3072,0xaa3eb072,0xb3d9b2a7,0x33d932a7,
0x2e1f3364,0x2e1f3364,0xb364ae1f,0xb364ae1f,0xb364ae1f,0xb364ae1f,0xae1fb364,0xae1fb364,0xae1fb364,0xae1fb364,0x33642e1f,0x33642e1f,0x33642e1f,0x33642e1f,0x2e1f3364,0x2e1f3364,
0x33642e1f,0x33642e1f,0x2e1f3364,0x2e1f3364,0x2e1f3364,0x2e1f3364,0xb364ae1f,0xb364ae1f,0xb364ae1f,0xb364ae1f,0xae1fb364,0xae1fb364,0xae1fb364,0xae1fb364,0x33642e1f,0x33642e1f,
0xaa3e32a7,0x2a3eb2a7,0xb3d9b072,0x33d93072,0xb072b3d9,0x307233d9,0x32a7aa3e,0xb2a72a3e,0x33d93072,0xb3d9b072,0xaa3e32a7,0x2a3eb2a7,0xb2a72a3e,0x32a7aa3e,0xb072b3d9,0x307233d9,
0x33d93072,0xb3d9b072,0xaa3e32a7,0x2a3eb2a7,0xb2a72a3e,0x32a7aa3e,0xb072b3d9,0x307233d9,0x2a3eb2a7,0xaa3e32a7,0x33d93072,0xb3d9b072,0x307233d9,0xb072b3d9,0xb2a72a3e,0x32a7aa3e,
0xb1a831a8,0xb1a831a8,0xb1a8b1a8,0xb1a8b1a8,0x31a8b1a8,0x31a8b1a8,0x31a831a8,0x31a831a8,0xb1a831a8,0xb1a831a8,0xb1a8b1a8,0xb1a8b1a8,0x31a8b1a8,0x31a8b1a8,0x31a831a8,0x31a831a8,
0x31a831a8,0x31a831a8,0xb1a831a8,0xb1a831a8,0xb1a8b1a8,0xb1a8b1a8,0x31a8b1a8,0x31a8b1a8,0x31a831a8,0x31a831a8,0xb1a831a8,0xb1a831a8,0xb1a8b1a8,0xb1a8b1a8,0x31a8b1a8,0x31a8b1a8,
0xb3d93072,0x33d9b072,0xaa3eb2a7,0x2a3e32a7,0x32a72a3e,0xb2a7aa3e,0xb07233d9,0x3072b3d9,0xaa3eb2a7,0x2a3e32a7,0x33d9b072,0xb3d93072,0xb07233d9,0x3072b3d9,0xb2a7aa3e,0x32a72a3e,
0x2a3e32a7,0xaa3eb2a7,0xb3d93072,0x33d9b072,0x3072b3d9,0xb07233d9,0x32a72a3e,0xb2a7aa3e,0xb3d93072,0x33d9b072,0xaa3eb2a7,0x2a3e32a7,0x32a72a3e,0xb2a7aa3e,0xb07233d9,0x3072b3d9,
0xb3642e1f,0xb3642e1f,0x2e1fb364,0x2e1fb364,0xae1f3364,0xae1f3364,0xb3642e1f,0xb3642e1f,0x3364ae1f,0x3364ae1f,0xae1f3364,0xae1f3364,0x2e1fb364,0x2e1fb364,0x3364ae1f,0x3364ae1f,
0xae1f3364,0xae1f3364,0xb3642e1f,0xb3642e1f,0x3364ae1f,0x3364ae1f,0xae1f3364,0xae1f3364,0x2e1fb364,0x2e1fb364,0x3364ae1f,0x3364ae1f,0xb3642e1f,0xb3642e1f,0x2e1fb364,0x2e1fb364,
0xb0722a3e,0x3072aa3e,0x32a7b3d9,0xb2a733d9,0xb3d932a7,0x33d9b2a7,0x2a3eb072,0xaa3e3072,0xb2a733d9,0x32a7b3d9,0xb0722a3e,0x3072aa3e,0xaa3e3072,0x2a3eb072,0xb3d932a7,0x33d9b2a7,
0xb2a733d9,0x32a7b3d9,0xb0722a3e,0x3072aa3e,0xaa3e3072,0x2a3eb072,0xb3d932a7,0x33d9b2a7,0x3072aa3e,0xb0722a3e,0xb2a733d9,0x32a7b3d9,0x33d9b2a7,0xb3d932a7,0xaa3e3072,0x2a3eb072,
0x0,0x0,0x3400b400,0x3400b400,0x0,0x0,0x3400b400,0x3400b400,0x0,0x0,0x3400b400,0x3400b400,0x0,0x0,0x3400b400,0x3400b400,
0xb4003400,0xb4003400,0x0,0x0,0xb4003400,0xb4003400,0x0,0x0,0xb4003400,0xb4003400,0x0,0x0,0xb4003400,0xb4003400,0x0,0x0,
0x3072aa3e,0xb0722a3e,0x32a7b3d9,0xb2a733d9,0x33d9b2a7,0xb3d932a7,0x2a3eb072,0xaa3e3072,0x32a7b3d9,0xb2a733d9,0xb0722a3e,0x3072aa3e,0x2a3eb072,0xaa3e3072,0xb3d932a7,0x33d9b2a7,
0xb2a733d9,0x32a7b3d9,0x3072aa3e,0xb0722a3e,0xaa3e3072,0x2a3eb072,0x33d9b2a7,0xb3d932a7,0x3072aa3e,0xb0722a3e,0x32a7b3d9,0xb2a733d9,0x33d9b2a7,0xb3d932a7,0x2a3eb072,0xaa3e3072,
0x3364ae1f,0x3364ae1f,0x2e1fb364,0x2e1fb364,0x2e1fb364,0x2e1fb364,0xb3642e1f,0xb3642e1f,0xb3642e1f,0xb3642e1f,0xae1f3364,0xae1f3364,0xae1f3364,0xae1f3364,0x3364ae1f,0x3364ae1f,
0xae1f3364,0xae1f3364,0x3364ae1f,0x3364ae1f,0x3364ae1f,0x3364ae1f,0x2e1fb364,0x2e1fb364,0x2e1fb364,0x2e1fb364,0xb3642e1f,0xb3642e1f,0xb3642e1f,0xb3642e1f,0xae1f3364,0xae1f3364,
0x33d9b072,0xb3d93072,0xaa3eb2a7,0x2a3e32a7,0xb2a7aa3e,0x32a72a3e,0xb07233d9,0x3072b3d9,0x2a3e32a7,0xaa3eb2a7,0x33d9b072,0xb3d93072,0x3072b3d9,0xb07233d9,0xb2a7aa3e,0x32a72a3e,
0x2a3e32a7,0xaa3eb2a7,0x33d9b072,0xb3d93072,0x3072b3d9,0xb07233d9,0xb2a7aa3e,0x32a72a3e,0xb3d93072,0x33d9b072,0x2a3e32a7,0xaa3eb2a7,0x32a72a3e,0xb2a7aa3e,0x3072b3d9,0xb07233d9,
0x31a8b1a8,0x31a8b1a8,0xb1a8b1a8,0xb1a8b1a8,0xb1a831a8,0xb1a831a8,0x31a831a8,0x31a831a8,0x31a8b1a8,0x31a8b1a8,0xb1a8b1a8,0xb1a8b1a8,0xb1a831a8,0xb1a831a8,0x31a831a8,0x31a831a8,
0x31a831a8,0x31a831a8,0x31a8b1a8,0x31a8b1a8,0xb1a8b1a8,0xb1a8b1a8,0xb1a831a8,0xb1a831a8,0x31a831a8,0x31a831a8,0x31a8b1a8,0x31a8b1a8,0xb1a8b1a8,0xb1a8b1a8,0xb1a831a8,0xb1a831a8,
0x2a3eb2a7,0xaa3e32a7,0xb3d9b072,0x33d93072,0x307233d9,0xb072b3d9,0x32a7aa3e,0xb2a72a3e,0xb3d9b072,0x33d93072,0xaa3e32a7,0x2a3eb2a7,0x32a7aa3e,0xb2a72a3e,0xb072b3d9,0x307233d9,
0x33d93072,0xb3d9b072,0x2a3eb2a7,0xaa3e32a7,0xb2a72a3e,0x32a7aa3e,0x307233d9,0xb072b3d9,0x2a3eb2a7,0xaa3e32a7,0xb3d9b072,0x33d93072,0x307233d9,0xb072b3d9,0x32a7aa3e,0xb2a72a3e,
0xae1fb364,0xae1fb364,0xb364ae1f,0xb364ae1f,0x33642e1f,0x33642e1f,0xae1fb364,0xae1fb364,0x2e1f3364,0x2e1f3364,0x33642e1f,0x33642e1f,0xb364ae1f,0xb364ae1f,0x2e1f3364,0x2e1f3364,
0x33642e1f,0x33642e1f,0xae1fb364,0xae1fb364,0x2e1f3364,0x2e1f3364,0x33642e1f,0x33642e1f,0xb364ae1f,0xb364ae1f,0x2e1f3364,0x2e1f3364,0xae1fb364,0xae1fb364,0xb364ae1f,0xb364ae1f,
0xb2a7b3d9,0x32a733d9,0xb072aa3e,0x30722a3e,0xaa3eb072,0x2a3e3072,0xb3d9b2a7,0x33d932a7,0x30722a3e,0xb072aa3e,0xb2a7b3d9,0x32a733d9,0x33d932a7,0xb3d9b2a7,0xaa3eb072,0x2a3e3072,
0x30722a3e,0xb072aa3e,0xb2a7b3d9,0x32a733d9,0x33d932a7,0xb3d9b2a7,0xaa3eb072,0x2a3e3072,0x32a733d9,0xb2a7b3d9,0x30722a3e,0xb072aa3e,0x2a3e3072,0xaa3eb072,0x33d932a7,0xb3d9b2a7,
};


__device__ __forceinline__ void wgmma_ss_n112(float* d, uint32_t al, uint32_t bl, int sc) {
  asm volatile("{\n.reg .pred p;\n.reg .b64 da, db;\nmov.b64 da, {%56, 0x40000040};\nmov.b64 db, {%57, 0x40000040};\nsetp.ne.b32 p, %58, 0;\n"
    "wgmma.mma_async.sync.aligned.m64n112k16.f32.bf16.bf16 "
    "{%0, %1, %2, %3, %4, %5, %6, %7, %8, %9, %10, %11, %12, %13, %14, %15, %16, %17, %18, %19, %20, %21, %22, %23, %24, %25, %26, %27, %28, %29, %30, %31, %32, %33, %34, %35, %36, %37, %38, %39, %40, %41, %42, %43, %44, %45, %46, %47, %48, %49, %50, %51, %52, %53, %54, %55}, "
    "da, db, p, 1, 1, 0, 1;\n}\n"
    : "+f"(d[0]), "+f"(d[1]), "+f"(d[2]), "+f"(d[3]), "+f"(d[4]), "+f"(d[5]), "+f"(d[6]), "+f"(d[7]), "+f"(d[8]), "+f"(d[9]), "+f"(d[10]), "+f"(d[11]), "+f"(d[12]), "+f"(d[13]), "+f"(d[14]), "+f"(d[15]), "+f"(d[16]), "+f"(d[17]), "+f"(d[18]), "+f"(d[19]), "+f"(d[20]), "+f"(d[21]), "+f"(d[22]), "+f"(d[23]), "+f"(d[24]), "+f"(d[25]), "+f"(d[26]), "+f"(d[27]), "+f"(d[28]), "+f"(d[29]), "+f"(d[30]), "+f"(d[31]), "+f"(d[32]), "+f"(d[33]), "+f"(d[34]), "+f"(d[35]), "+f"(d[36]), "+f"(d[37]), "+f"(d[38]), "+f"(d[39]), "+f"(d[40]), "+f"(d[41]), "+f"(d[42]), "+f"(d[43]), "+f"(d[44]), "+f"(d[45]), "+f"(d[46]), "+f"(d[47]), "+f"(d[48]), "+f"(d[49]), "+f"(d[50]), "+f"(d[51]), "+f"(d[52]), "+f"(d[53]), "+f"(d[54]), "+f"(d[55])
    : "r"(al), "r"(bl), "r"(sc));
}

__device__ __forceinline__ void wgmma_ss_n128(float* d, uint32_t al, uint32_t bl, int sc) {
  asm volatile("{\n.reg .pred p;\n.reg .b64 da, db;\nmov.b64 da, {%64, 0x40000040};\nmov.b64 db, {%65, 0x40000040};\nsetp.ne.b32 p, %66, 0;\n"
    "wgmma.mma_async.sync.aligned.m64n128k16.f32.bf16.bf16 "
    "{%0, %1, %2, %3, %4, %5, %6, %7, %8, %9, %10, %11, %12, %13, %14, %15, %16, %17, %18, %19, %20, %21, %22, %23, %24, %25, %26, %27, %28, %29, %30, %31, %32, %33, %34, %35, %36, %37, %38, %39, %40, %41, %42, %43, %44, %45, %46, %47, %48, %49, %50, %51, %52, %53, %54, %55, %56, %57, %58, %59, %60, %61, %62, %63}, "
    "da, db, p, 1, 1, 0, 1;\n}\n"
    : "+f"(d[0]), "+f"(d[1]), "+f"(d[2]), "+f"(d[3]), "+f"(d[4]), "+f"(d[5]), "+f"(d[6]), "+f"(d[7]), "+f"(d[8]), "+f"(d[9]), "+f"(d[10]), "+f"(d[11]), "+f"(d[12]), "+f"(d[13]), "+f"(d[14]), "+f"(d[15]), "+f"(d[16]), "+f"(d[17]), "+f"(d[18]), "+f"(d[19]), "+f"(d[20]), "+f"(d[21]), "+f"(d[22]), "+f"(d[23]), "+f"(d[24]), "+f"(d[25]), "+f"(d[26]), "+f"(d[27]), "+f"(d[28]), "+f"(d[29]), "+f"(d[30]), "+f"(d[31]), "+f"(d[32]), "+f"(d[33]), "+f"(d[34]), "+f"(d[35]), "+f"(d[36]), "+f"(d[37]), "+f"(d[38]), "+f"(d[39]), "+f"(d[40]), "+f"(d[41]), "+f"(d[42]), "+f"(d[43]), "+f"(d[44]), "+f"(d[45]), "+f"(d[46]), "+f"(d[47]), "+f"(d[48]), "+f"(d[49]), "+f"(d[50]), "+f"(d[51]), "+f"(d[52]), "+f"(d[53]), "+f"(d[54]), "+f"(d[55]), "+f"(d[56]), "+f"(d[57]), "+f"(d[58]), "+f"(d[59]), "+f"(d[60]), "+f"(d[61]), "+f"(d[62]), "+f"(d[63])
    : "r"(al), "r"(bl), "r"(sc));
}

__device__ __forceinline__ void wgmma_rs_n64(float* d, const uint32_t* a, uint32_t bl, int sc) {
  asm volatile("{\n.reg .pred p;\n.reg .b64 db;\nmov.b64 db, {%36, 0x40000040};\nsetp.ne.b32 p, %37, 0;\n"
    "wgmma.mma_async.sync.aligned.m64n64k16.f32.bf16.bf16 "
    "{%0, %1, %2, %3, %4, %5, %6, %7, %8, %9, %10, %11, %12, %13, %14, %15, %16, %17, %18, %19, %20, %21, %22, %23, %24, %25, %26, %27, %28, %29, %30, %31}, "
    "{%32, %33, %34, %35}, db, p, 1, 1, 1;\n}\n"
    : "+f"(d[0]), "+f"(d[1]), "+f"(d[2]), "+f"(d[3]), "+f"(d[4]), "+f"(d[5]), "+f"(d[6]), "+f"(d[7]), "+f"(d[8]), "+f"(d[9]), "+f"(d[10]), "+f"(d[11]), "+f"(d[12]), "+f"(d[13]), "+f"(d[14]), "+f"(d[15]), "+f"(d[16]), "+f"(d[17]), "+f"(d[18]), "+f"(d[19]), "+f"(d[20]), "+f"(d[21]), "+f"(d[22]), "+f"(d[23]), "+f"(d[24]), "+f"(d[25]), "+f"(d[26]), "+f"(d[27]), "+f"(d[28]), "+f"(d[29]), "+f"(d[30]), "+f"(d[31])
    : "r"(a[0]), "r"(a[1]), "r"(a[2]), "r"(a[3]), "r"(bl), "r"(sc));
}


namespace {

constexpr int SLOT = 16384;
constexpr int OFF_MISC = 14 * SLOT;
constexpr int SMEM_BYTES = OFF_MISC + 3072;
constexpr int OFF_TBL = 0;
constexpr int OFF_SM = 22528;
constexpr int OFF_U = 24576;
constexpr int OFF_P2 = 49152;
constexpr int OFF_WM = 65536;
constexpr int OFF_X = 81920;
constexpr int OFF_WR = 98304;
constexpr int OFF_WI = 108544;
constexpr int OFF_SC = 118784;
constexpr int OFF_M3 = 119808;
constexpr int OFF_WS = 125952;
constexpr int OFF_RED = 130048;
constexpr int OFF_RED1 = OFF_P2;
constexpr int OFF_GV = OFF_P2 + 2048;
constexpr int UP = 1296;
constexpr int OFF_BAR = OFF_MISC;
constexpr int OFF_GB = OFF_MISC + 768;
constexpr int B_DONE = 0;
constexpr int B_FULL = 16;
constexpr int B_TBL = 30, B_W = 31;
constexpr int B_IN = 32;
constexpr int B_E1 = 40, B_X = 42, B_GV = 43;
constexpr int B_A = 44;
constexpr int B_AR = 60;
constexpr int B_PEER = 76;
constexpr int B_INB = 77;
constexpr int B_PF = 85, B_X1 = 86, B_RDY = 87;

constexpr uint32_t TAGY = 0x00010000u, TAGM = 0x00010001u;
constexpr int SPIN = 1 << 21;

struct Early {
    const __nv_bfloat16 *c, *wmod;
    uint32_t *X, *mod, *flag;
    const uint32_t* tbl;
};
struct Params {
    uint4* E;
    const __nv_bfloat16* x;
    const __nv_bfloat16 *wrp, *wip, *w1p, *w3p, *w2p;
    __nv_bfloat16* out;
    CUtensorMap xin, w1a, w3a, w1, w3, w2a, w2b, wr, wi, wrs, wis, ea;
};

}

__device__ __align__(1024) uint4 g_E[128 * 128 * 8];
__device__ __align__(128) uint32_t g_X[128 * 8];
__device__ __align__(128) uint32_t g_mod[3072];
__device__ __align__(128) uint32_t g_flag[3 * 1024];
#define RB 4
#define NB 3
#define C_SEND 4
#define D_X 1450
#define D_E1 2700
#define D_E2 2180
#define D_E3 815
#define D_W4 20
#define D_SK 350
#define D_G 430
#define D_A1 350
#define D_S2 740
#define D_PACE 520
#define D_N1 50
#define D_WM 400
#define D_A2 380
#define D_ST 185
#define D_MOD 2950
#define R_INFL 4
#define ORDER() bar_arrive(0, 32)
#define TRAP() asm volatile("trap;")
#define DELAY(n) do { if ((n) > 0) { const uint32_t c0_ = clk32(); while (clk32() - c0_ < (uint32_t)(n)) { } } } while (0)

namespace {

__device__ __forceinline__ uint32_t clk32() { uint32_t c; asm volatile("mov.u32 %0, %%clock;" : "=r"(c)::"memory"); return c; }
__device__ __forceinline__ uint32_t smem_u32(const void* p) { return (uint32_t)__cvta_generic_to_shared(p); }
__device__ __forceinline__ void mbar_init(uint32_t bar, int cnt) { asm volatile("mbarrier.init.shared::cta.b64 [%0], %1;" ::"r"(bar), "r"(cnt) : "memory"); }
__device__ __forceinline__ void mbar_expect(uint32_t bar, int bytes) { asm volatile("mbarrier.arrive.expect_tx.shared::cta.b64 _, [%0], %1;" ::"r"(bar), "r"(bytes) : "memory"); }
__device__ __forceinline__ void mbar_arrive(uint32_t bar) { asm volatile("mbarrier.arrive.shared::cta.b64 _, [%0];" ::"r"(bar) : "memory"); }
__device__ __forceinline__ void mbar_wait(uint32_t bar, uint32_t par = 0) {
    asm volatile("{\n.reg .pred p;\nW_LOOP:\nmbarrier.try_wait.parity.shared::cta.b64 p, [%0], %1;\n@!p bra.uni W_LOOP;\n}\n" ::"r"(bar), "r"(par) : "memory");
}
__device__ __forceinline__ void mbar_wait2(uint32_t b0, uint32_t p0, uint32_t b1, uint32_t p1) {
    asm volatile("{\n.reg .pred p, q;\nW_LOOP:\nmbarrier.try_wait.parity.shared::cta.b64 p, [%0], %1;\nmbarrier.try_wait.parity.shared::cta.b64 q, [%2], %3;\n"
                 "and.pred p, p, q;\n@!p bra.uni W_LOOP;\n}\n" ::"r"(b0), "r"(p0), "r"(b1), "r"(p1) : "memory");
}
__device__ __forceinline__ void mbar_arrive_if(bool c, uint32_t bar) {
    asm volatile("{\n.reg .pred p;\nsetp.ne.u32 p, %1, 0;\n@p mbarrier.arrive.shared::cta.b64 _, [%0];\n}\n" ::"r"(bar), "r"((uint32_t)c) : "memory");
}
__device__ __forceinline__ bool bar_and(int id, int n, bool v) {
    uint32_t r;
    asm volatile("{\n.reg .pred p, q;\nsetp.ne.u32 p, %3, 0;\nbarrier.cta.red.and.aligned.pred q, %1, %2, p;\nselp.u32 %0, 1, 0, q;\n}\n" : "=r"(r) : "r"(id), "r"(n), "r"((uint32_t)v) : "memory");
    return r;
}
__device__ __forceinline__ bool elect() {
    uint32_t r;
    asm volatile("{\n.reg .pred p;\nelect.sync _|p, 0xffffffff;\nselp.u32 %0, 1, 0, p;\n}\n" : "=r"(r));
    return r;
}
__device__ __forceinline__ void bar_sync(int id, int n) { asm volatile("bar.sync %0, %1;" ::"r"(id), "r"(n) : "memory"); }
__device__ __forceinline__ void bar_arrive(int id, int n) { asm volatile("bar.arrive %0, %1;" ::"r"(id), "r"(n) : "memory"); }
__device__ __forceinline__ void tma2d(uint32_t dst, const CUtensorMap* m, int c0, int c1, uint32_t bar) {
    asm volatile("cp.async.bulk.tensor.2d.shared::cluster.global.mbarrier::complete_tx::bytes [%0], [%1, {%3, %4}], [%2];" ::"r"(dst), "l"(m), "r"(bar), "r"(c0), "r"(c1) : "memory");
}
__device__ __forceinline__ void tma3d(uint32_t dst, const CUtensorMap* m, int c0, int c1, int c2, uint32_t bar) {
    asm volatile("cp.async.bulk.tensor.3d.shared::cluster.global.mbarrier::complete_tx::bytes [%0], [%1, {%3, %4, %5}], [%2];" ::"r"(dst), "l"(m), "r"(bar), "r"(c0), "r"(c1), "r"(c2) : "memory");
}
__device__ __forceinline__ void bulk_g2s(uint32_t dst, const void* src, int bytes, uint32_t bar) {
    asm volatile("cp.async.bulk.shared::cluster.global.mbarrier::complete_tx::bytes [%0], [%1], %2, [%3];" ::"r"(dst), "l"(src), "r"(bytes), "r"(bar) : "memory");
}
__device__ __forceinline__ void prefetch_map(const CUtensorMap* m) { asm volatile("prefetch.tensormap [%0];" ::"l"(m) : "memory"); }
__device__ __forceinline__ void prefetch_l2(const void* p, int bytes) { asm volatile("cp.async.bulk.prefetch.L2.global [%0], %1;" ::"l"(p), "r"(bytes) : "memory"); }
__device__ __forceinline__ void wg_fence() { asm volatile("wgmma.fence.sync.aligned;" ::: "memory"); }
__device__ __forceinline__ void wg_commit() { asm volatile("wgmma.commit_group.sync.aligned;" ::: "memory"); }
template <int N> __device__ __forceinline__ void wg_wait() { asm volatile("wgmma.wait_group.sync.aligned %0;" ::"n"(N) : "memory"); }
__device__ __forceinline__ uint4 ld_rlx(const void* p) {
    uint4 v;
    asm volatile("ld.relaxed.gpu.global.v4.u32 {%0,%1,%2,%3}, [%4];" : "=r"(v.x), "=r"(v.y), "=r"(v.z), "=r"(v.w) : "l"(p) : "memory");
    return v;
}
__device__ __forceinline__ void st_rlx(void* p, uint4 v) {
    asm volatile("st.relaxed.gpu.global.v4.u32 [%0], {%1,%2,%3,%4};" ::"l"(p), "r"(v.x), "r"(v.y), "r"(v.z), "r"(v.w) : "memory");
}
__device__ __forceinline__ uint32_t ld_rlx32(const void* p) { uint32_t v; asm volatile("ld.relaxed.gpu.global.u32 %0, [%1];" : "=r"(v) : "l"(p) : "memory"); return v; }
__device__ __forceinline__ uint32_t lds32(uint32_t a) { uint32_t v; asm volatile("ld.shared.u32 %0, [%1];" : "=r"(v) : "r"(a) : "memory"); return v; }
__device__ __forceinline__ void st_rlx32(void* p, uint32_t v) { asm volatile("st.relaxed.gpu.global.u32 [%0], %1;" ::"l"(p), "r"(v) : "memory"); }
__device__ __forceinline__ uint4 lds128(uint32_t a) { uint4 v; asm volatile("ld.shared.v4.u32 {%0,%1,%2,%3}, [%4];" : "=r"(v.x), "=r"(v.y), "=r"(v.z), "=r"(v.w) : "r"(a) : "memory"); return v; }
__device__ __forceinline__ void sts128(uint32_t a, uint4 v) { asm volatile("st.shared.v4.u32 [%0], {%1,%2,%3,%4};" ::"r"(a), "r"(v.x), "r"(v.y), "r"(v.z), "r"(v.w) : "memory"); }
__device__ __forceinline__ float lds32f(uint32_t a) { float v; asm volatile("ld.shared.f32 %0, [%1];" : "=f"(v) : "r"(a) : "memory"); return v; }
__device__ __forceinline__ void sts32f(uint32_t a, float v) { asm volatile("st.shared.f32 [%0], %1;" ::"r"(a), "f"(v) : "memory"); }
__device__ __forceinline__ float lds_bf(uint32_t a) { uint16_t v; asm volatile("ld.shared.u16 %0, [%1];" : "=h"(v) : "r"(a) : "memory"); return __uint_as_float((uint32_t)v << 16); }
__device__ __forceinline__ uint4 ldsm4(uint32_t a) { uint4 v; asm volatile("ldmatrix.sync.aligned.m8n8.x4.shared.b16 {%0,%1,%2,%3}, [%4];" : "=r"(v.x), "=r"(v.y), "=r"(v.z), "=r"(v.w) : "r"(a) : "memory"); return v; }
__device__ __forceinline__ uint4 ldsm4t(uint32_t a) { uint4 v; asm volatile("ldmatrix.sync.aligned.m8n8.x4.trans.shared.b16 {%0,%1,%2,%3}, [%4];" : "=r"(v.x), "=r"(v.y), "=r"(v.z), "=r"(v.w) : "r"(a) : "memory"); return v; }
__device__ __forceinline__ void stsm4(uint32_t a, uint4 v) { asm volatile("stmatrix.sync.aligned.m8n8.x4.shared.b16 [%0], {%1,%2,%3,%4};" ::"r"(a), "r"(v.x), "r"(v.y), "r"(v.z), "r"(v.w) : "memory"); }
__device__ __forceinline__ uint32_t pack(float lo, float hi) { uint32_t r; asm("cvt.rn.bf16x2.f32 %0, %1, %2;" : "=r"(r) : "f"(hi), "f"(lo)); return r; }
__device__ __forceinline__ float blo(uint32_t w) { return __uint_as_float(w << 16); }
__device__ __forceinline__ float bhi(uint32_t w) { return __uint_as_float(w & 0xFFFF0000u); }
__device__ __forceinline__ float rbf(float x) { return blo(pack(x, 0.f)); }
__device__ __forceinline__ uint32_t comp(const uint4& v, int i) { return i == 0 ? v.x : i == 1 ? v.y : i == 2 ? v.z : v.w; }
__device__ __forceinline__ void mma0(float* d, const uint4& a, uint32_t b0, uint32_t b1) {
    asm("mma.sync.aligned.m16n8k16.row.col.f32.bf16.bf16.f32 {%0,%1,%2,%3}, {%4,%5,%6,%7}, {%8,%9}, {%10,%10,%10,%10};"
        : "=f"(d[0]), "=f"(d[1]), "=f"(d[2]), "=f"(d[3]) : "r"(a.x), "r"(a.y), "r"(a.z), "r"(a.w), "r"(b0), "r"(b1), "f"(0.f));
}
__device__ __forceinline__ void mma1(float* d, const uint4& a, uint32_t b0, uint32_t b1) {
    asm("mma.sync.aligned.m16n8k16.row.col.f32.bf16.bf16.f32 {%0,%1,%2,%3}, {%4,%5,%6,%7}, {%8,%9}, {%0,%1,%2,%3};"
        : "+f"(d[0]), "+f"(d[1]), "+f"(d[2]), "+f"(d[3]) : "r"(a.x), "r"(a.y), "r"(a.z), "r"(a.w), "r"(b0), "r"(b1));
}
__device__ __forceinline__ void mmac(float* d, const uint4& a, uint32_t b0, uint32_t b1, const float* c) {
    asm("mma.sync.aligned.m16n8k16.row.col.f32.bf16.bf16.f32 {%0,%1,%2,%3}, {%4,%5,%6,%7}, {%8,%9}, {%10,%11,%12,%13};"
        : "=f"(d[0]), "=f"(d[1]), "=f"(d[2]), "=f"(d[3]) : "r"(a.x), "r"(a.y), "r"(a.z), "r"(a.w), "r"(b0), "r"(b1), "f"(c[0]), "f"(c[1]), "f"(c[2]), "f"(c[3]));
}
__device__ __forceinline__ void ln_finish(float s, float q, float& mean, float& rstd) {
    float m = s * (1.f / 512.f), var = fmaxf(fmaf(-m, m, q * (1.f / 512.f)), 0.f), sd;
    asm("sqrt.approx.ftz.f32 %0, %1;" : "=f"(sd) : "f"(rbf(rbf(var) + 1e-5f)));
    asm("rcp.approx.ftz.f32 %0, %1;" : "=f"(rstd) : "f"(rbf(sd)));
    mean = rbf(m);
}
__device__ __forceinline__ float treduce8(float* v, int lane) {
    bool u = lane & 16;
#pragma unroll
    for (int i = 0; i < 4; i++) { float s = u ? v[i] : v[i + 4], k = u ? v[i + 4] : v[i]; v[i] = k + __shfl_xor_sync(~0u, s, 16); }
    u = lane & 8;
#pragma unroll
    for (int i = 0; i < 2; i++) { float s = u ? v[i] : v[i + 2], k = u ? v[i + 2] : v[i]; v[i] = k + __shfl_xor_sync(~0u, s, 8); }
    u = lane & 4;
    float s = u ? v[0] : v[1], k = u ? v[1] : v[0];
    return k + __shfl_xor_sync(~0u, s, 4);
}
__device__ __forceinline__ void ln_stats(const float (&xf)[4][8], float* mean, float* rstd, uint32_t sb, int warp, int lane) {
    float v[8];
#pragma unroll
    for (int r = 0; r < 4; r++) {
        float s = xf[r][0], q = s * s;
#pragma unroll
        for (int i = 1; i < 8; i++) { s += xf[r][i]; q = fmaf(xf[r][i], xf[r][i], q); }
        v[r] = s; v[4 + r] = q;
    }
    sts32f(sb + OFF_RED + (warp * 32 + lane) * 4, treduce8(v, lane));
    bar_sync(12, 320);
    float p[8];
#pragma unroll
    for (int w = 0; w < 8; w++) p[w] = lds32f(sb + OFF_RED + (w * 32 + lane) * 4);
    float tot = ((p[0] + p[1]) + (p[2] + p[3])) + ((p[4] + p[5]) + (p[6] + p[7]));
    float oth = __shfl_xor_sync(~0u, tot, 16), m, rs;
    ln_finish(lane < 16 ? tot : oth, lane < 16 ? oth : tot, m, rs);
    m *= -rs;
#pragma unroll
    for (int r = 0; r < 4; r++) {
        mean[r] = __shfl_sync(~0u, m, 4 * r + (lane & 3));
        rstd[r] = __shfl_sync(~0u, rs, 4 * r + (lane & 3));
    }
}

__device__ __forceinline__ uint32_t packh(float lo, float hi) { uint32_t r; asm("cvt.rn.f16x2.f32 %0, %1, %2;" : "=r"(r) : "f"(hi), "f"(lo)); return r; }
__device__ __forceinline__ uint32_t hfma(uint32_t a, uint32_t b, uint32_t c) { uint32_t d; asm("fma.rn.f16x2 %0, %1, %2, %3;" : "=r"(d) : "r"(a), "r"(b), "r"(c)); return d; }
__device__ __forceinline__ uint32_t hfms(uint32_t a, uint32_t b, uint32_t c) {
    uint32_t d; asm("{\n.reg .b32 n;\nneg.f16x2 n, %1;\nfma.rn.f16x2 %0, n, %2, %3;\n}" : "=r"(d) : "r"(a), "r"(b), "r"(c)); return d;
}
__device__ __forceinline__ uint32_t hmul(uint32_t a, uint32_t b) { uint32_t d; asm("mul.rn.f16x2 %0, %1, %2;" : "=r"(d) : "r"(a), "r"(b)); return d; }
__device__ __forceinline__ uint32_t hadd(uint32_t a, uint32_t b) { uint32_t d; asm("add.rn.f16x2 %0, %1, %2;" : "=r"(d) : "r"(a), "r"(b)); return d; }
__device__ __forceinline__ uint32_t hsub(uint32_t a, uint32_t b) { uint32_t d; asm("sub.rn.f16x2 %0, %1, %2;" : "=r"(d) : "r"(a), "r"(b)); return d; }
__device__ __forceinline__ uint32_t hswap(uint32_t a) { return __byte_perm(a, a, 0x1032); }
__device__ __forceinline__ void sts32(uint32_t a, uint32_t v) { asm volatile("st.shared.u32 [%0], %1;" ::"r"(a), "r"(v) : "memory"); }
constexpr uint32_t H_PM = 0xBC003C00u, H_MP = 0x3C00BC00u;
__device__ __forceinline__ void hm0(uint32_t* d, const uint4& a, uint32_t b0, uint32_t b1) {
    asm("mma.sync.aligned.m16n8k16.row.col.f16.f16.f16.f16 {%0,%1}, {%2,%3,%4,%5}, {%6,%7}, {%8,%8};"
        : "=r"(d[0]), "=r"(d[1]) : "r"(a.x), "r"(a.y), "r"(a.z), "r"(a.w), "r"(b0), "r"(b1), "r"(0u));
}
__device__ __forceinline__ void hm1(uint32_t* d, const uint4& a, uint32_t b0, uint32_t b1) {
    asm("mma.sync.aligned.m16n8k16.row.col.f16.f16.f16.f16 {%0,%1}, {%2,%3,%4,%5}, {%6,%7}, {%0,%1};"
        : "+r"(d[0]), "+r"(d[1]) : "r"(a.x), "r"(a.y), "r"(a.z), "r"(a.w), "r"(b0), "r"(b1));
}
__device__ __forceinline__ void hmf(float* d, const uint4& a, uint32_t b0, uint32_t b1) {
    asm("mma.sync.aligned.m16n8k16.row.col.f32.f16.f16.f32 {%0,%1,%2,%3}, {%4,%5,%6,%7}, {%8,%9}, {%10,%10,%10,%10};"
        : "=f"(d[0]), "=f"(d[1]), "=f"(d[2]), "=f"(d[3]) : "r"(a.x), "r"(a.y), "r"(a.z), "r"(a.w), "r"(b0), "r"(b1), "f"(0.f));
}
__device__ __forceinline__ void cmulc(uint32_t a, uint32_t c, uint32_t cc, uint32_t ss, uint32_t& r, uint32_t& m) { r = hfma(c, ss, hmul(a, cc)); m = hfms(a, ss, hmul(c, cc)); }
__device__ __forceinline__ void cmul(uint32_t a, uint32_t c, uint32_t cc, uint32_t ss, uint32_t& r, uint32_t& m) { r = hfms(c, ss, hmul(a, cc)); m = hfma(a, ss, hmul(c, cc)); }
__device__ __forceinline__ int expo(uint32_t absbits) { return min(max((int)(absbits >> 23), 30), 222); }
__device__ __forceinline__ float pow2(int e) { return __uint_as_float((uint32_t)(e + 127) << 23); }

__device__ __forceinline__ void fft_fwd(const uint4 (&br)[2], const uint4 (&bi)[2], const uint4* K, uint32_t (&out)[2][2][4]) {
    uint32_t vr[4][2], vi[4][2];
#pragma unroll
    for (int n = 0; n < 4; n++) {
        const int h = n >> 1;
        uint32_t b0 = comp(br[h], 2 * (n & 1)), b1 = comp(br[h], 2 * (n & 1) + 1);
        hm0(vr[n], K[3 * h + 1], b0, b1);
        hm0(vi[n], K[3 * h + 2], b0, b1);
    }
#pragma unroll
    for (int n = 0; n < 4; n++) {
        const int h = n >> 1;
        uint32_t b0 = comp(bi[h], 2 * (n & 1)), b1 = comp(bi[h], 2 * (n & 1) + 1);
        hm1(vr[n], K[3 * h], b0, b1);
        hm1(vi[n], K[3 * h + 1], b0, b1);
    }
#pragma unroll
    for (int kh = 0; kh < 2; kh++) {
        uint32_t zr[4], zi[4];
#pragma unroll
        for (int r = 0; r < 4; r++) {
            const int n = r >> 1, hi = r & 1;
            cmulc(kh ? hsub(vr[n][hi], vr[n + 2][hi]) : hadd(vr[n][hi], vr[n + 2][hi]), kh ? hsub(vi[n][hi], vi[n + 2][hi]) : hadd(vi[n][hi], vi[n + 2][hi]),
                  comp(K[10 + 2 * kh], r), comp(K[11 + 2 * kh], r), zr[r], zi[r]);
        }
        const uint4 Ar = make_uint4(zr[0], zr[1], zr[2], zr[3]), Ai = make_uint4(zi[0], zi[1], zi[2], zi[3]);
#pragma unroll
        for (int n = 0; n < 4; n++) {
            uint32_t o[2];
            hm0(o, Ar, K[6 + n].x, K[6 + n].y);
            hm1(o, Ai, K[6 + n].z, K[6 + n].w);
            out[n >> 1][n & 1][2 * kh] = o[0]; out[n >> 1][n & 1][2 * kh + 1] = o[1];
        }
    }
}

__device__ __forceinline__ void fft_inv(const uint4 (&v)[2][2], const uint4* K, uint32_t ure, uint32_t uim) {
    uint32_t z[2][4][2];
#pragma unroll
    for (int kh = 0; kh < 2; kh++)
#pragma unroll
        for (int r = 0; r < 4; r++) hm0(z[kh][r], K[2 * (r & 1)], comp(v[0][0], 2 * kh + (r >> 1)), comp(v[0][1], 2 * kh + (r >> 1)));
#pragma unroll
    for (int kh = 0; kh < 2; kh++)
#pragma unroll
        for (int r = 0; r < 4; r++) hm1(z[kh][r], K[2 * (r & 1) + 1], comp(v[1][0], 2 * kh + (r >> 1)), comp(v[1][1], 2 * kh + (r >> 1)));
    uint32_t wr[2][4], wi[2][4];
#pragma unroll
    for (int kh = 0; kh < 2; kh++)
#pragma unroll
        for (int r = 0; r < 4; r++) cmul(z[kh][r][0], z[kh][r][1], comp(K[4 + 2 * kh], r), comp(K[5 + 2 * kh], r), wr[kh][r], wi[kh][r]);
    uint32_t oR[2][2][2], oI[2][2][2];
#pragma unroll
    for (int h = 0; h < 2; h++) {
        uint32_t r[4], m[4];
#pragma unroll
        for (int q = 0; q < 4; q++) { r[q] = h ? hsub(wr[0][q], wr[1][q]) : hadd(wr[0][q], wr[1][q]); m[q] = h ? hsub(wi[0][q], wi[1][q]) : hadd(wi[0][q], wi[1][q]); }
        const uint4 Ar = make_uint4(r[0], r[1], r[2], r[3]), Ai = make_uint4(m[0], m[1], m[2], m[3]);
#pragma unroll
        for (int nt = 0; nt < 2; nt++) {
            hm0(oR[h][nt], Ar, comp(K[8 + 3 * h], 2 * nt), comp(K[8 + 3 * h], 2 * nt + 1));
            hm0(oI[h][nt], Ar, comp(K[9 + 3 * h], 2 * nt), comp(K[9 + 3 * h], 2 * nt + 1));
            hm1(oR[h][nt], Ai, comp(K[10 + 3 * h], 2 * nt), comp(K[10 + 3 * h], 2 * nt + 1));
            hm1(oI[h][nt], Ai, comp(K[8 + 3 * h], 2 * nt), comp(K[8 + 3 * h], 2 * nt + 1));
        }
    }
#pragma unroll
    for (int nt = 0; nt < 2; nt++) {
        sts128(ure + nt * 640, make_uint4(oR[0][nt][0], oR[0][nt][1], oR[1][nt][0], oR[1][nt][1]));
        sts128(uim + nt * 640, make_uint4(oI[0][nt][0], oI[0][nt][1], oI[1][nt][0], oI[1][nt][1]));
    }
}

__device__ __forceinline__ void col128a(const uint32_t* d, const uint4* K, const uint4& w, uint32_t* zr, uint32_t* zi) {
    uint32_t cr[2], ci[2], y[2][2];
    hm0(cr, K[0], d[0], d[1]); hm0(ci, K[2], d[0], d[1]);
    hm1(cr, K[1], d[2], d[3]); hm1(ci, K[3], d[2], d[3]);
    cmulc(cr[0], ci[0], K[4].x, K[4].z, zr[0], zi[0]); cmulc(cr[1], ci[1], K[4].y, K[4].w, zr[1], zi[1]);
    const uint4 A = make_uint4(zr[0], zr[1], zi[0], zi[1]);
    hm0(cr, A, K[5].x, K[5].y); hm0(ci, A, K[5].z, K[5].w);
    cmul(cr[0], ci[0], w.x, w.z, zr[0], zi[0]); cmul(cr[1], ci[1], w.y, w.w, zr[1], zi[1]);
    hm0(y[0], K[6], zr[0], zi[0]); hm0(y[1], K[6], zr[1], zi[1]);
    cmul(y[0][0], y[0][1], K[7].x, K[7].z, zr[0], zi[0]); cmul(y[1][0], y[1][1], K[7].y, K[7].w, zr[1], zi[1]);
}
__device__ __forceinline__ void col128b(const uint32_t* r0, const uint32_t* m0, const uint32_t* r1, const uint32_t* m1, const uint4* K, uint32_t (&o)[4][2]) {
    const uint4 Ar = make_uint4(r0[0], r1[0], r0[1], r1[1]), Ai = make_uint4(m0[0], m1[0], m0[1], m1[1]);
#pragma unroll
    for (int i = 0; i < 4; i++) { hm0(o[i], Ar, K[8 + i].x, K[8 + i].y); hm1(o[i], Ai, K[8 + i].z, K[8 + i].w); }
}

__device__ __forceinline__ float silu_mul(float h, float u) {
    float t, hu = h * u;
    asm("tanh.approx.f32 %0, %1;" : "=f"(t) : "f"(h));
    return fmaf(hu, t, hu);
}
__device__ __forceinline__ int slice_f0(int j) { return j < 7 ? 176 * j : 1216; }
__device__ __forceinline__ int slice_na(int j) { return j < 6 ? 112 : 96; }

}

__global__ void __cluster_dims__(2, 1, 1) __launch_bounds__(384, 1) fused_kernel(const Early q0, const __grid_constant__ Params p) {
    extern __shared__ __align__(1024) unsigned char smem_raw[];
    const uint32_t sb = smem_u32(smem_raw);
    const int b = blockIdx.x, tid = threadIdx.x;
    if (tid >= 256) {
        const uint32_t r = (tid & 31) + 2 * (tid & 96);
        asm volatile("cp.async.cg.shared.global [%0], [%1], 16;\ncp.async.cg.shared.global [%0+512], [%1+196608], 16;\n"
                     "cp.async.cg.shared.global [%0+4096], [%1+1572864], 16;\ncp.async.cg.shared.global [%0+4608], [%1+1769472], 16;"
                     ::"r"(sb + OFF_WM + r * 16), "l"(q0.wmod + (r * 3072 + 8 * b)) : "memory");
    }
    const int warp = __shfl_sync(~0u, tid >> 5, 0), lane = tid & 31, g = lane >> 2, t = lane & 3;
    const uint32_t bars = sb + OFF_BAR;
    const int grp = b >> 3, jf = b & 7, ke = b & 1;
    const uint32_t peer_sb = sb ^ 0x01000000u;
    const int rho = b >> 4, gam = b & 15;
    const int k1 = rho ? rho : (gam & 8), cg = rho ? gam : (gam & 7);
    const bool mir = rho && gam >= 8;
    const int wlo = mir ? (16 - k1) * 257 + 481 - 32 * cg : k1 * 257 + 32 * cg;
    const bool sdir = mir || rho == 0;
    const int wsp = sdir ? k1 * 257 + 256 : (16 - k1) * 257;
    const int gp = 4 * (g & 1) + (g >> 1);
    const uint32_t xoff = (uint32_t)(2 * t * 128 + b) * 512 + 64 * warp + 8 * gp;
    uint4 xr[4];
    uint32_t clk0 = 0;
    int ea = 0;
    uint32_t tag = 0;

    uint4* eline = p.E + ((16 * warp + 2 * t) * 128 + b) * 8 + (g ^ (((b >> 3) & 3) * 2 + (b & 1)));
#define SILU_C() do { const float f0_ = blo(cc), f1_ = bhi(cc); \
        sts32(sb + OFF_SC + (tid & 0x78) * 8 + (tid & 3) * 16 + (tid & 4) * 2 + (tid >> 7) * 4, pack(__fdividef(f0_, 1.f + __expf(-f0_)), __fdividef(f1_, 1.f + __expf(-f1_)))); \
        if (warp == 7) sts32(sb + OFF_SM + 40, 1 + (epoch & 1)); \
        bar_arrive(13, 384); } while (0)
#define WM_PF() do { _Pragma("unroll") for (int i_ = 0; i_ < 4; i_++) prefetch_l2(q0.wmod + (4 * b + i_) * 3072 + 1024, 4096); } while (0)
#define W_ISSUE() do { mbar_expect(bars + 8 * B_W, (cg & 7) ? 20480 : 24576); \
        tma3d(sb + OFF_WR, &p.wr, wlo & ~7, 0, 0, bars + 8 * B_W); tma3d(sb + OFF_WI, &p.wi, wlo & ~7, 0, 0, bars + 8 * B_W); \
        if (!(cg & 7)) { tma2d(sb + OFF_WS, &p.wrs, wsp & ~7, 0, bars + 8 * B_W); tma2d(sb + OFF_WS + 2048, &p.wis, wsp & ~7, 0, bars + 8 * B_W); } } while (0)

    if (warp >= 8) {
        const int u = tid - 256;
        clk0 = clk32();
        const int r0 = (u >> 5) * 64 + lane;
        if (warp == 8 && lane < 8) st_rlx32(q0.mod + 8 * b + lane, 0u);
        if (tid == 256) { st_rlx(q0.flag + 2048 + 8 * b, make_uint4(0, 0, 0, 0)); st_rlx(q0.flag + 2052 + 8 * b, make_uint4(0, 0, 0, 0)); }
        if (warp == 11 && t < 2) st_rlx32(q0.mod + 1024 + 16 * b + 2 * g + t, 0u);
        bar_sync(13, 384);
        tag = lds32(sb + OFF_SM + 40);
        uint4 A[4];
#pragma unroll
        for (int k = 0; k < 4; k++) A[k] = lds128(sb + OFF_SC + (u >> 5) * 256 + k * 64 + 16 * t);
        asm volatile("cp.async.wait_all;" ::: "memory");
        __syncwarp();
        float m[4][4];
#pragma unroll
        for (int i = 0; i < 4; i++) {
            const uint4 w = ldsm4t(sb + OFF_WM + (r0 + 32 * (i & 1) + 256 * (i >> 1)) * 16);
            mma0(m[i], A[2 * (i & 1)], w.x, w.y);
            mma1(m[i], A[2 * (i & 1) + 1], w.z, w.w);
        }
        if (lane < 8) sts32f(sb + OFF_GV + ((2 * t + g) * 4 + warp - 8) * 4, g ? (m[0][1] + m[1][1]) + (m[2][3] + m[3][3]) : (m[0][0] + m[1][0]) + (m[2][2] + m[3][2]));
        bar_sync(1, 384);
        if (warp == 9 && elect()) { prefetch_l2(p.wrp + b * 4112, 8224); prefetch_l2(p.wip + b * 4112, 8224); }
        if (warp == 8 && lane < 8) {
            uint4 a = lds128(sb + OFF_GV + lane * 16);
            float r = rbf((__uint_as_float(a.x) + __uint_as_float(a.y)) + (__uint_as_float(a.z) + __uint_as_float(a.w)));
            if (b >= 64) r = rbf(1.f + r);
            st_rlx32(q0.mod + 8 * b + lane, __float_as_uint(r) | tag);
        }
        uint4 ms, mc;
        while (clk32() - clk0 < (uint32_t)D_MOD) { }
#pragma unroll 1
        for (int spin = 0;; spin++) {
            ms = ld_rlx(q0.mod + 4 * u); mc = ld_rlx(q0.mod + 512 + 4 * u);
            if (ms.x & ms.y & ms.z & ms.w & mc.x & mc.y & mc.z & mc.w & tag) break;
            if (spin > SPIN) TRAP();
        }
        {
            const uint32_t mx = max(max(max(ms.x << 1, ms.y << 1), max(ms.z << 1, ms.w << 1)), max(max(mc.x << 1, mc.y << 1), max(mc.z << 1, mc.w << 1)));
            sts32(sb + OFF_SM + (warp - 8) * 4, __reduce_max_sync(~0u, mx));
            bar_sync(7, 128);
            const uint4 m4 = lds128(sb + OFF_SM);
            ea = expo(max(max(m4.x, m4.y), max(m4.z, m4.w)) >> 1);
            const float al = pow2(126 - ea), a4 = 4.f * al;
            asm volatile("st.shared.v2.u32 [%0], {%1, %2};\nst.shared.v2.u32 [%0+1296], {%3, %4};" ::"r"(sb + OFF_U + 16 * UP + 80 * (u >> 3) + 8 * (u & 7)),
                         "r"(packh(a4 * __uint_as_float(ms.x), a4 * __uint_as_float(ms.y))), "r"(packh(a4 * __uint_as_float(ms.z), a4 * __uint_as_float(ms.w))),
                         "r"(packh(al * __uint_as_float(mc.x), al * __uint_as_float(mc.y))), "r"(packh(al * __uint_as_float(mc.z), al * __uint_as_float(mc.w))) : "memory");
        }
        if (warp == 9) { bar_arrive(8, 384); if (elect()) W_ISSUE(); }
        else bar_sync(8, 384);
    } else {
        clk0 = clk32();
        const uint32_t cc = ld_rlx32(q0.c + 2 * tid);
        uint32_t epoch = 0;
        if (warp == 7) epoch = ld_rlx32(q0.flag + 1024);
        if (warp == 0 && elect()) {
            mbar_init(bars + 8 * B_W, 1); mbar_init(bars + 8 * B_TBL, 1); mbar_init(bars + 8 * B_X, 1);
            asm volatile("fence.mbarrier_init.release.cluster;" ::: "memory");
            prefetch_map(&p.xin);
            mbar_expect(bars + 8 * B_TBL, 43 * 512);
            mbar_expect(bars + 8 * B_X, 16384);
            bulk_g2s(sb + OFF_TBL, q0.tbl, 31 * 512, bars + 8 * B_TBL);
            bulk_g2s(sb + OFF_TBL + 31 * 512, q0.tbl + (31 + 12 * k1) * 128, 12 * 512, bars + 8 * B_TBL);
            uint32_t chk;
            asm("mapa.shared::cluster.u32 %0, %1, %2;" : "=r"(chk) : "r"(sb), "r"(ke ^ 1));
            if ((sb & 0x3FFFF) != 1024 || chk != peer_sb) TRAP();
        }
        if (warp > 0 && warp < 7 && elect()) {
            const int b0 = (0x4D2C203C1000ull >> (8 * (warp - 1))) & 255, tx = warp == 4 ? 3584 : warp == 5 ? 8192 : 2048;
#pragma unroll
            for (int i = 0; i < 16; i++) if (i < 10 || (warp & 1) || (warp == 2 && i < 14)) mbar_init(bars + 8 * (b0 + i), warp == 1 ? 2 : 1);
            if (warp >= 4) {
#pragma unroll
                for (int i = 0; i < 16; i++) if (i < 8 || warp == 5) mbar_expect(bars + 8 * (b0 + i), tx);
            }
            if (warp == 6) { mbar_init(bars + 8 * B_PEER, 1); mbar_init(bars + 8 * B_X1, 8); mbar_init(bars + 8 * B_RDY, 16); mbar_init(bars + 8 * B_GV, 1); mbar_expect(bars + 8 * B_GV, 256); }
            asm volatile("fence.mbarrier_init.release.cluster;" ::: "memory");
        }
        if (warp == 3) {
#pragma unroll 1
            for (int i = 10; i >= 0; i--) if (elect()) prefetch_map(&p.w1a + i);
        }
        if (tid == 0) { st_rlx(q0.X + 8 * b, make_uint4(0, 0, 0, 0)); st_rlx(q0.X + 8 * b + 4, make_uint4(0, 0, 0, 0)); }
        if (warp == 0 && elect()) {
            while (clk32() - clk0 < (uint32_t)D_X) { }
            asm volatile("cp.async.bulk.tensor.4d.shared::cluster.global.mbarrier::complete_tx::bytes [%0], [%1, {0, 0, 0, %3}], [%2];" ::"r"(sb + OFF_X), "l"(&p.xin),
                         "r"(bars + 8 * B_X), "r"(b) : "memory");
        }
        SILU_C();
        bar_sync(1, 384);
    }

    const uint32_t tbl = sb + OFF_TBL + lane * 16;
    if (warp >= 8) {
        if (warp != 9) {
            bar_sync(3, 384);
            mbar_wait(bars + 8 * B_W);
            uint32_t mx = 0;
#define ABSMAX(v_) do { mx = __vmaxu2(mx, __vmaxu2(__vmaxu2((v_).x & 0x7FFF7FFFu, (v_).y & 0x7FFF7FFFu), __vmaxu2((v_).z & 0x7FFF7FFFu, (v_).w & 0x7FFF7FFFu))); } while (0)
            if (!(cg & 7) && warp != 8) {
#pragma unroll 1
                for (int q = 0; q < 4; q++) { const uint4 w = lds128(sb + OFF_WS + (warp & 1) * 2048 + q * 512 + lane * 16); ABSMAX(w); }
            }
#pragma unroll 1
            for (int i = warp == 8 ? 0 : warp - 9; i < 10; i += 3) {
                const int arr = i >= 5, ch = i - 5 * arr;
                uint4 w[4];
#pragma unroll
                for (int q = 0; q < 4; q++) w[q] = ldsm4t(sb + OFF_WR + arr * (OFF_WI - OFF_WR) + (mir ? 127 - 32 * q - lane : 32 * q + lane) * 80 + 16 * ch);
#pragma unroll
                for (int q = 0; q < 4; q++) { stsm4(sb + OFF_U + (8 * ch + (lane & 7)) * 528 + arr * 256 + (4 * q + (lane >> 3)) * 16, w[q]); ABSMAX(w[q]); }
            }
            sts32(sb + OFF_SM + 16 + (warp & 3) * 4, __reduce_max_sync(~0u, max(mx << 16, mx & 0xFFFF0000u)));
            if (warp != 8) bar_arrive(14, 352);
        }
        if (warp == 8) {
            bar_sync(14, 352);
            const uint4 m4 = lds128(sb + OFF_SM + 16);
            const int eb = expo(max(m4.x, max(m4.z, m4.w)));
            if (lane == 0) st_rlx32(q0.flag + 2048 + 8 * b, (uint32_t)(eb << 2) | tag);
            if ((b & ~8) == 0) {
                uint4 K[12];
                float w[8];
                uint32_t d[4], zr[2], zi[2], o[4][2];
#pragma unroll
                for (int i = 0; i < 12; i++) K[i] = lds128(tbl + (31 + i) * 512);
#pragma unroll
                for (int i = 0; i < 8; i++) w[i] = pow2(127 - eb) * lds_bf(sb + OFF_WS + (i >> 2) * 2048 + (g + 32 * t + 8 * ((i >> 1) & 1) + 16 * (i & 1)) * 16 + 2 * (wsp & 7));
                uint32_t* const xp = q0.X + (8 * t + g) * 8 + (b >> 3);
#pragma unroll 1
                for (int spin = 0;; spin++) {
#pragma unroll
                    for (int i = 0; i < 4; i++) d[i] = ld_rlx32(xp + 256 * i);
                    if (__all_sync(~0u, d[0] & d[1] & d[2] & d[3] & 1)) break;
                    if (spin > SPIN) TRAP();
                }
                col128a(d, K, make_uint4(packh(w[0], w[1]), packh(w[2], w[3]), packh(w[4], w[5]), packh(w[6], w[7])), zr, zi);
                col128b(zr, zi, zr, zi, K, o);
#pragma unroll
                for (int i = 0; i < 4; i++) st_rlx32(xp + 256 * i, o[i][0] & ~1u);
                if (b == 0 && lane == 0) st_rlx32(q0.flag + 1024, tag);
            }
        } else if (warp == 9) {
            bar_sync(3, 384);
            if (elect()) WM_PF();
            clk0 = clk32();
#pragma unroll 1
            for (int i = 0; i < 4; i++) {
                while (clk32() - clk0 < (uint32_t)(i < 3 ? (3 + i) * D_PACE : D_E1)) { }
                if (i == 3 && elect()) {
                    mbar_expect(bars + 8 * B_E1, 16384);
                    bulk_g2s(sb + OFF_P2, p.E + b * 1024, 16384, bars + 8 * B_E1);
                }
                if (elect()) { prefetch_l2(p.w1p + (i * 128 + b) * 1376, 2752); prefetch_l2(p.w3p + (i * 128 + b) * 1376, 2752); }
            }
            bar_arrive(15, 96);
        }
        int eg = 126;
        if (warp >= 10) {
            const int hf = warp & 1;
            uint4 A[8];
#pragma unroll
            for (int k = 0; k < 8; k++) A[k] = lds128(sb + OFF_SC + hf * 512 + k * 64 + 16 * t);
            bar_sync(15, 96);
            DELAY(D_WM);
#pragma unroll 4
            for (int k = 0; k < 16; k++)
                asm volatile("cp.async.cg.shared.global [%0], [%1], 16;" ::"r"(sb + OFF_WM + hf * 8192 + (8 * k + g) * 64 + ((t ^ ((g >> 1) & 3)) << 4)),
                             "l"(q0.wmod + (256 * ke + 128 * hf + 8 * k + g) * 3072 + 1024 + 16 * (b & ~1) + 8 * t) : "memory");
            asm volatile("cp.async.wait_all;" ::: "memory");
            __syncwarp();
            uint4 w[16];
            float m[4][4];
#pragma unroll
            for (int k = 0; k < 16; k++) w[k] = ldsm4t(sb + OFF_WM + hf * 8192 + (k >> 1) * 1024 + (lane & 15) * 64 + (((2 * (k & 1) + (lane >> 4)) ^ ((lane >> 1) & 3)) << 4));
#pragma unroll
            for (int k = 0; k < 16; k++) {
                if (k < 2) { mma0(m[2 * k], A[0], w[k].x, w[k].y); mma0(m[2 * k + 1], A[0], w[k].z, w[k].w); }
                else { mma1(m[2 * (k & 1)], A[k >> 1], w[k].x, w[k].y); mma1(m[2 * (k & 1) + 1], A[k >> 1], w[k].z, w[k].w); }
            }
            if (ke) {
#pragma unroll
                for (int k = 0; k < 4; k++) { m[k][0] = m[k][2]; m[k][1] = m[k][3]; }
            }
            if (lane < 16) {
                const uint32_t dst = (g >> 1) == ke ? sb : peer_sb;
                asm volatile("st.async.weak.shared::cluster.mbarrier::complete_tx::bytes.v2.f32 [%0], {%1, %2}, [%3];" ::"r"(dst + OFF_SM + 1024 + (lane & 7) * 32 + (2 * ke + hf) * 8),
                             "f"(g & 2 ? (g & 1 ? m[3][0] : m[2][0]) : (g & 1 ? m[1][0] : m[0][0])), "f"(g & 2 ? (g & 1 ? m[3][1] : m[2][1]) : (g & 1 ? m[1][1] : m[0][1])),
                             "r"(dst + OFF_BAR + 8 * B_GV) : "memory");
            }
        } else {
            bar_sync(9, 320);
            if (warp == 8) {
                uint32_t e[4];
#pragma unroll 1
                for (int spin = 0;; spin++) {
#pragma unroll
                    for (int i = 0; i < 4; i++) e[i] = ld_rlx32(q0.flag + 2048 + 8 * (lane + 32 * i));
                    if (__all_sync(~0u, e[0] & e[1] & e[2] & e[3] & tag)) break;
                    if (spin > SPIN) TRAP();
                }
                eg = __reduce_max_sync(~0u, max(max(e[0], e[1]), max(e[2], e[3]))) >> 2;
#pragma unroll
                for (int i = 0; i < 4; i++) { const float f = pow2(max((int)(e[i] >> 2) - eg, -60)); sts32(sb + OFF_SM + 512 + (lane + 32 * i) * 4, packh(f, f)); }
                bar_arrive(11, 288);
            } else if (elect()) prefetch_l2(p.w2p + b * 5504, 11008);
        }
        if (warp != 9) {
        mbar_wait(bars + 8 * B_GV);
        if (warp == 11) {
            const uint32_t ra = sb + OFF_SM + 1024 + g * 32 + (t & 1) * 4;
            float r = rbf((lds32f(ra) + lds32f(ra + 8)) + (lds32f(ra + 16) + lds32f(ra + 24)));
            if ((b >> 5) == 2) r = rbf(1.f + r);
            r *= (b >> 5) == 3 ? 2.f : 0.5f;
            if (t < 2) st_rlx32(q0.mod + 1024 + 16 * b + 2 * g + t, (__float_as_uint(r) & ~3u) | tag);
        }
        DELAY(D_G);
#pragma unroll 1
        for (int hq = warp == 8 ? 0 : warp - 9; hq < 4; hq += (warp == 11 ? 1 : 4)) {
            uint4 mm[4];
#pragma unroll 1
            for (int spin = 0;; spin++) {
                uint32_t ok = tag;
#pragma unroll
                for (int q = 0; q < 4; q++) { mm[q] = ld_rlx(q0.mod + 1024 + hq * 512 + ((q * 128) ^ (hq == 3 ? ke * 256 : 0)) + lane * 4); ok &= mm[q].x & mm[q].y & mm[q].z & mm[q].w; }
                if (__all_sync(~0u, ok)) break;
                if (spin > SPIN) TRAP();
            }
            const float g0 = pow2(warp == 8 ? ea - 126 : 0), g1 = pow2(eg - 126);
            if (hq < 3) {
#pragma unroll
                for (int q = 0; q < 4; q++)
                    sts128(sb + OFF_M3 + hq * 2048 + q * 512 + lane * 16,
                           make_uint4(__float_as_uint(__uint_as_float(mm[q].x) * g0 * g1), __float_as_uint(__uint_as_float(mm[q].y) * g0 * g1),
                                      __float_as_uint(__uint_as_float(mm[q].z) * g0 * g1), __float_as_uint(__uint_as_float(mm[q].w) * g0 * g1)));
            } else {
#pragma unroll
                for (int q = 0; q < 2; q++)
                    asm volatile("st.shared.v2.u32 [%0], {%1, %2};" ::"r"(sb + OFF_GB + q * 256 + lane * 8), "r"(__byte_perm(mm[q].x, mm[q].y, 0x7632)), "r"(__byte_perm(mm[q].z, mm[q].w, 0x7632)) : "memory");
            }
            if (hq < 3) { if (hq) bar_arrive(12, 320); else bar_arrive(10, 288); }
        }
        }
        else bar_sync(6, 288);
    } else {
        mbar_wait(bars + 8 * B_TBL);
        asm volatile("mov.b64 %0, %0;" : "+l"(eline));
        uint4 K[15];
#pragma unroll
        for (int i = 0; i < 14; i++) K[i] = lds128(tbl + (2 + i) * 512);
        {
            const uint4 M0 = lds128(tbl), M1 = lds128(tbl + 512);
            const uint32_t xa = sb + OFF_X + warp * 2048 + (lane & 15) * 128;
            mbar_wait(bars + 8 * B_X);
            float g0[4], g1[4], sm[4];
            uint4 B[4];
#pragma unroll
            for (int k = 0; k < 4; k++) {
                const uint4 A = ldsm4(xa + (((2 * k + (lane >> 4)) ^ (lane & 7)) << 4));
                if (k == 0) { mma0(g0, A, A.x, A.z); mma0(g1, A, A.y, A.w); mma0(sm, A, 0x3F803F80u, 0x3F803F80u); }
                else { mma1(g0, A, A.x, A.z); mma1(g1, A, A.y, A.w); mma1(sm, A, 0x3F803F80u, 0x3F803F80u); }
            }
#pragma unroll
            for (int k = 0; k < 4; k++) B[k] = ldsm4t(xa + (((2 * k + (lane >> 4)) ^ (lane & 7)) << 4));
            if (t == (g >> 1))
                asm volatile("st.shared.v2.f32 [%0], {%1, %2};\nst.shared.v2.f32 [%0+640], {%3, %4};" ::"r"(sb + OFF_RED1 + g * 80 + warp * 8),
                             "f"(sm[0]), "f"((g & 1) ? g0[1] : g0[0]), "f"(sm[2]), "f"((g & 1) ? g1[3] : g1[2]) : "memory");
            bar_sync(2, 256);
            const uint4 r0 = lds128(sb + OFF_RED1 + (lane & 15) * 80 + (lane >> 4) * 32), r1 = lds128(sb + OFF_RED1 + (lane & 15) * 80 + (lane >> 4) * 32 + 16);
            float s = (__uint_as_float(r0.x) + __uint_as_float(r0.z)) + (__uint_as_float(r1.x) + __uint_as_float(r1.z));
            float q = (__uint_as_float(r0.y) + __uint_as_float(r0.w)) + (__uint_as_float(r1.y) + __uint_as_float(r1.w));
            s += __shfl_xor_sync(~0u, s, 16); q += __shfl_xor_sync(~0u, q, 16);
            float mean, rstd, mn[4], rs[4];
            ln_finish(s, q, mean, rstd);
#pragma unroll
            for (int r = 0; r < 4; r++) { mn[r] = __shfl_sync(~0u, -mean, 2 * t + (r & 1) + 8 * (r >> 1)); rs[r] = __shfl_sync(~0u, rstd, 2 * t + (r & 1) + 8 * (r >> 1)); }
            const uint4 A = make_uint4(pack(__uint_as_float(M0.x) * rs[0], __uint_as_float(M0.y) * rs[1]), pack(__uint_as_float(M0.z) * rs[0], __uint_as_float(M0.w) * rs[1]),
                                       pack(__uint_as_float(M1.x) * rs[2], __uint_as_float(M1.y) * rs[3]), pack(__uint_as_float(M1.z) * rs[2], __uint_as_float(M1.w) * rs[3]));
            float c0[4], u[8][4];
            mma0(c0, A, pack(mn[0], mn[1]), pack(mn[2], mn[3]));
#pragma unroll
            for (int i = 0; i < 8; i++) mmac(u[i], A, comp(B[i >> 1], 2 * (i & 1)), comp(B[i >> 1], 2 * (i & 1) + 1), c0);
            const uint32_t ua = sb + OFF_U + (lane & 15) * UP + 160 * warp + 16 * (lane >> 4);
#pragma unroll
            for (int k = 0; k < 4; k++)
                stsm4(ua + 80 * (k >> 1) + 32 * (k & 1), make_uint4(packh(u[2 * k][0], u[2 * k][1]), packh(u[2 * k][2], u[2 * k][3]),
                                                                    packh(u[2 * k + 1][0], u[2 * k + 1][1]), packh(u[2 * k + 1][2], u[2 * k + 1][3])));
        }
        bar_sync(8, 384);
        const uint32_t mw = 4 * (g + 72 * t), mr = 4 * (280 - g - 72 * t), mr0 = mr + (g == 0 ? 32 : 0);
        {
            const uint32_t ul = sb + OFF_U + 80 * (lane & 15) + 16 * (lane >> 4);
            uint4 br[2], bi[2];
#pragma unroll
            for (int h = 0; h < 2; h++) {
                const uint4 sc = ldsm4t(ul + 17 * UP + 32 * h), r = ldsm4t(ul + warp * UP + 32 * h), m = ldsm4t(ul + (8 + warp) * UP + 32 * h);
                uint4 sh = make_uint4(0, 0, 0, 0);
                if (warp == 0) sh = ldsm4t(ul + 16 * UP + 32 * h);
                br[h] = make_uint4(hfma(r.x, sc.x, sh.x), hfma(r.y, sc.y, sh.y), hfma(r.z, sc.z, sh.z), hfma(r.w, sc.w, sh.w));
                bi[h] = make_uint4(hmul(m.x, sc.x), hmul(m.y, sc.y), hmul(m.z, sc.z), hmul(m.w, sc.w));
            }
            clk0 = clk32();
            bar_arrive(3, 384);
            if (warp == 4) while (clk32() - clk0 < (uint32_t)D_W4) { }
            uint32_t o[2][2][4];
            fft_fwd(br, bi, K, o);
            if (warp == 0) {
                const uint32_t ms = sb + OFF_M3;
#pragma unroll
                for (int i = 0; i < 8; i++) sts32(ms + mw + 32 * i, o[1][i >> 2][i & 3]);
                if (lane == 0) {
                    sts32(ms + 4 * 288, o[0][0][0]);
                    *(volatile uint64_t*)(q0.X + 8 * b) = (uint64_t)((o[1][0][0] & 0xFFFFu) | 1u) | ((uint64_t)((o[1][0][0] >> 16) | 1u) << 32);
                }
                __syncwarp();
#pragma unroll
                for (int i = 0; i < 8; i++) {
                    const uint32_t zm = lds32(ms + (i ? mr : mr0) - 32 * i), z = o[0][i >> 2][i & 3];
                    o[0][i >> 2][i & 3] = hfma(zm, H_PM, z);
                    o[1][i >> 2][i & 3] = hswap(hfma(z, H_MP, zm));
                }
            }
#pragma unroll
            for (int i = 0; i < 4; i++) {
                uint32_t* w = o[i >> 1][i & 1];
                w[2 * (i & 1)] = (w[2 * (i & 1)] & ~TAGM) | 1u;
                st_rlx(eline + (8 * (i >> 1) + (i & 1)) * 1024, make_uint4(w[0], w[1], w[2], w[3]));
            }
        }
        ORDER();
        {
#pragma unroll
            for (int i = 0; i < 12; i++) K[i] = lds128(tbl + (31 + i) * 512);
            const uint32_t pa = sb + OFF_P2 + (8 * t + g) * 128 + ((warp ^ (2 * t + (g & 1))) << 4);
            uint4 v[4];
            uint4 wf[4];
            bar_sync(14, 352);
            {
                const int k20 = g + 32 * t;
                const int sg = mir ? -1 : 1;
                const uint32_t wa = sb + OFF_U + ((wlo & 7) + (mir ? 31 - warp : warp)) * 528 + lane * 16;
                const uint4 m4 = lds128(sb + OFF_SM + 16);
                const float be = pow2(126 - expo(max(m4.x, max(m4.z, m4.w)))), bi = sg * be;
#pragma unroll
                for (int c = 0; c < 4; c++) {
                    const uint4 w = ldsm4(wa + sg * 528 * 8 * c);
                    float f[8] = {blo(w.x), bhi(w.x), blo(w.y), bhi(w.y), blo(w.z), bhi(w.z), blo(w.w), bhi(w.w)};
                    if (c == 0 && warp == 0 && rho && !(cg & 7)) {
#pragma unroll
                        for (int i = 0; i < 4; i++) {
                            const int k2 = k20 + 8 * (i >> 1) + 16 * (i & 1);
                            const uint32_t a = sb + OFF_WS + (mir ? k2 : 127 - k2) * 16 + 2 * (wsp & 7);
                            f[i] = 0.5f * (f[i] + lds_bf(a));
                            f[4 + i] = 0.5f * (f[4 + i] - lds_bf(a + 2048));
                        }
                    }
                    wf[c] = make_uint4(packh(be * f[0], be * f[1]), packh(be * f[2], be * f[3]), packh(bi * f[4], bi * f[5]), packh(bi * f[6], bi * f[7]));
                }
            }
            {
                uint32_t z = 0;
#pragma unroll
                for (int c = 0; c < 4; c++) z |= wf[c].x & wf[c].y & wf[c].z & wf[c].w;
                if (z == 0x7FFF7FFFu) sts32(sb + OFF_SM + 44, z);
            }
            mbar_wait(bars + 8 * B_E1);
#pragma unroll
            for (int i = 0; i < 4; i++) v[i] = lds128(pa + i * 4096);
            bar_arrive(9, 320);
            clk0 = clk32();
            int spin = 0;
#define TW(i) (((b & 1) ? v[i].z : v[i].x) ^ 1u)
            if (__builtin_expect(__any_sync(~0u, (TW(0) | TW(1) | TW(2) | TW(3)) & TAGM), 0)) {
#pragma unroll 1
                do {
#pragma unroll
                    for (int i = 0; i < 4; i++) if (TW(i) & TAGM) v[i] = ld_rlx((const char*)(p.E + b * 1024) + (pa - sb - OFF_P2) + i * 4096);
                    if (++spin > SPIN) TRAP();
                } while (__any_sync(~0u, (TW(0) | TW(1) | TW(2) | TW(3)) & TAGM));
            }
            if (warp >= 4) while (clk32() - clk0 < (uint32_t)D_S2) { }
            uint32_t zr[4][2], zi[4][2], o0[4][2], o1[4][2];
#pragma unroll
            for (int c = 0; c < 4; c++) {
                const uint32_t d[4] = {comp(v[0], c), comp(v[1], c), comp(v[2], c), comp(v[3], c)};
                col128a(d, K, wf[c], zr[c], zi[c]);
            }
            col128b(zr[0], zi[0], zr[1], zi[1], K, o0);
            col128b(zr[2], zi[2], zr[3], zi[3], K, o1);
            const uint32_t m0 = (b & 1) ? ~0u : ~TAGM, m2 = (b & 1) ? ~TAGM : ~0u;
#pragma unroll
            for (int i = 0; i < 4; i++) sts128(pa + i * 4096, make_uint4(o0[i][0] & m0, o0[i][1], o1[i][0] & m2, o1[i][1]));
            bar_sync(4 + (warp >> 2), 128);
            const int ro = ((tid & 127) >> 3) + 16 * ((tid >> 2) & 1), vo = ro * 8 + 4 * (((tid >> 7) ^ (tid >> 2)) & 1) + t;
#pragma unroll
            for (int i = 0; i < 4; i++) v[i] = lds128(sb + OFF_P2 + (vo + 256 * i) * 16);
#pragma unroll
            for (int i = 0; i < 4; i++) st_rlx(p.E + b * 1024 + vo + 256 * i, v[i]);
        }
        ORDER();
#pragma unroll
        for (int i = 0; i < 15; i++) K[i] = lds128(tbl + (16 + i) * 512);
        {
            bar_sync(11, 288);
            uint32_t fj[4];
            asm volatile("ld.shared.v2.u32 {%0, %1}, [%4];\nld.shared.v2.u32 {%2, %3}, [%4+32];" : "=r"(fj[0]), "=r"(fj[1]), "=r"(fj[2]), "=r"(fj[3]) : "r"(sb + OFF_SM + 512 + (16 * warp + 2 * t) * 4) : "memory");
            uint4 v[2][2], xv = make_uint4(0, 0, 0, 0);
            int spin = 0;
            while (clk32() - clk0 < (uint32_t)D_E2) { }
            v[0][0] = ld_rlx(eline); v[0][1] = ld_rlx(eline + 1024); v[1][0] = ld_rlx(eline + 8 * 1024); v[1][1] = ld_rlx(eline + 9 * 1024);
            if (tid == 0) xv = ld_rlx(q0.X + 8 * b);
#define E2_BAD() __any_sync(~0u, (v[0][0].x | v[0][1].z | v[1][0].x | v[1][1].z | xv.x | xv.y) & 1u)
            if (__builtin_expect(E2_BAD(), 0))
#pragma unroll 1
            do {
                if (v[0][0].x & 1u) v[0][0] = ld_rlx(eline);
                if (v[0][1].z & 1u) v[0][1] = ld_rlx(eline + 1024);
                if (v[1][0].x & 1u) v[1][0] = ld_rlx(eline + 8 * 1024);
                if (v[1][1].z & 1u) v[1][1] = ld_rlx(eline + 9 * 1024);
                if (tid == 0) xv = ld_rlx(q0.X + 8 * b);
                if (++spin > SPIN) TRAP();
            } while (E2_BAD());
            bar_arrive(6, 288);
#pragma unroll
            for (int i = 0; i < 4; i++) {
                uint4& q = v[i >> 1][i & 1];
                q = make_uint4(hmul(q.x, fj[i]), hmul(q.y, fj[i]), hmul(q.z, fj[i]), hmul(q.w, fj[i]));
            }
            if (warp == 0) {
                const uint32_t ms = sb + OFF_WR;
                uint32_t z[8];
#pragma unroll
                for (int i = 0; i < 8; i++) {
                    const uint32_t a = comp(v[0][i >> 2], i & 3), c = hswap(comp(v[1][i >> 2], i & 3));
                    z[i] = hfma(c, H_MP, a);
                    if (i == 0 && lane == 0) z[0] = __byte_perm(a, c, 0x7610);
                    sts32(ms + (i ? mr : mr0) - 32 * i, hfma(a, H_PM, c));
                }
                if (lane == 0) sts32(ms, __byte_perm(hmul(xv.x, fj[0]), hmul(xv.y, fj[2]), 0x5410));
                __syncwarp();
                v[0][0] = make_uint4(z[0], z[1], z[2], z[3]); v[0][1] = make_uint4(z[4], z[5], z[6], z[7]);
#pragma unroll
                for (int e = 0; e < 2; e++) v[1][e] = make_uint4(lds32(ms + mw + 128 * e), lds32(ms + mw + 128 * e + 32), lds32(ms + mw + 128 * e + 64), lds32(ms + mw + 128 * e + 96));
            }
            const uint32_t uo = sb + OFF_U + 160 * t + 16 * g;
            fft_inv(v, K, uo + warp * UP, uo + (8 + warp) * UP);
        }
        {
#pragma unroll
            for (int r = 0; r < 4; r++) xr[r] = lds128(sb + OFF_X + warp * 2048 + (2 * t + (r & 1) + 8 * (r >> 1)) * 128 + ((gp ^ (2 * t + (r & 1))) << 4));
            bar_sync(10, 288);
            float xf[4][8], mean[4], rstd[4];
            uint4 mg[2], mh[2], mk[2];
            const uint32_t ma = sb + OFF_M3 + (64 * warp + 8 * gp) * 4;
            mg[0] = lds128(ma); mg[1] = lds128(ma + 16);
            const uint32_t ua = sb + OFF_U + ((lane & 7) + 8 * (lane >> 4)) * UP + 160 * warp + 16 * ((lane >> 3) & 1);
#pragma unroll
            for (int i = 0; i < 4; i++) {
                uint4 A = ldsm4t(ua + 32 * i);
                float y0[4], y1[4];
                hmf(y0, A, K[14].x, K[14].y); hmf(y1, A, K[14].z, K[14].w);
#pragma unroll
                for (int e = 0; e < 2; e++) {
                    float ga = __uint_as_float(comp(mg[i >> 1], 2 * (i & 1) + e));
#pragma unroll
                    for (int r = 0; r < 4; r++) {
                        float y = (r < 2 ? y0 : y1)[2 * e + (r & 1)];
                        uint32_t xw2 = comp(xr[r], i);
                        xf[r][2 * i + e] = fmaf(ga, y, e ? bhi(xw2) : blo(xw2));
                    }
                }
            }
            ln_stats(xf, mean, rstd, sb, warp, lane);
#pragma unroll
            for (int i = 0; i < 2; i++) { mh[i] = lds128(ma + 2048 + 16 * i); mk[i] = lds128(ma + 4096 + 16 * i); }
            if (lane < 2) asm volatile("mbarrier.arrive.relaxed.cluster.shared::cluster.b64 _, [%0];" ::"r"((lane ? peer_sb : sb) + OFF_BAR + 8 * B_RDY) : "memory");
            uint4* const e3 = p.E + ((16 * warp + 2 * t) * 128 + b) * 8 + (gp ^ jf);
            uint4 ho[4];
            if (warp >= 4) DELAY(D_N1);
#pragma unroll
            for (int r = 0; r < 4; r++) {
                float h[8];
#pragma unroll
                for (int i = 0; i < 8; i++) h[i] = fmaf(fmaf(xf[r][i], rstd[r], mean[r]), __uint_as_float(comp(mk[i >> 2], i & 3)), __uint_as_float(comp(mh[i >> 2], i & 3)));
                ho[r] = make_uint4(pack(h[0], h[1]) | ((r & 1) ? 0u : TAGY), pack(h[2], h[3]), pack(h[4], h[5]) | ((r & 1) ? TAGY : 0u), pack(h[6], h[7]));
            }
            clk0 = clk32();
            while (clk32() - clk0 < (uint32_t)(warp * D_ST)) { }
#pragma unroll
            for (int r = 0; r < 4; r++) {
                st_rlx(e3 + ((r & 1) + 8 * (r >> 1)) * 1024, ho[r]);
            }
#pragma unroll
            for (int r = 0; r < 4; r++) xr[r] = make_uint4(pack(xf[r][0], xf[r][1]), pack(xf[r][2], xf[r][3]), pack(xf[r][4], xf[r][5]), pack(xf[r][6], xf[r][7]));
        }
    }

    constexpr unsigned long long WS = 0x8D7C6B5A4938ull;
#define A_ISSUE(c) asm volatile("cp.async.bulk.tensor.2d.shared::cluster.global.mbarrier::complete_tx::bytes.multicast::cluster [%0], [%1, {%3, %4}], [%2], %5;" \
            ::"r"(sb + (c) * SLOT + wg * 8192 + ke * 4096), "l"(&p.ea), "r"(bars + 8 * (B_A + 8 * wg + (c))), "r"(256 * grp), "r"(16 * (c) + 8 * wg + 4 * ke), "h"((uint16_t)3) : "memory")
#define A_RETRY(c) do { const uint32_t ab_ = bars + 8 * (B_A + 8 * wg + (c)); mbar_expect(ab_, 8192); \
            tma2d(sb + (c) * SLOT + wg * 8192, &p.ea, 256 * grp, 16 * (c) + 8 * wg, ab_); \
            tma2d(sb + (c) * SLOT + wg * 8192 + 4096, &p.ea, 256 * grp, 16 * (c) + 8 * wg + 4, ab_); } while (0)
    if (warp >= 8) {
        asm volatile("setmaxnreg.dec.sync.aligned.u32 40;");
        if (warp == 8) {
            mbar_wait(bars + 8 * B_RDY);
            clk0 = clk32();
#pragma unroll 1
            for (int n = 0; n < 16; n++) {
                const int wg = n & 1, c = n >> 1;
                while (clk32() - clk0 < (uint32_t)(D_E3 + wg * D_SK + (c < 2 ? c * D_A1 : 2 * D_A1 + (c - 2) * D_A2))) { }
                if (elect()) A_ISSUE(c);
            }
        } else if (warp != 9) {
            const int wg = warp & 1;
#pragma unroll 1
            for (int c = 1; c < 8; c++) {
#pragma unroll 1
                for (int spin = 0;; spin++) {
                    mbar_wait(bars + 8 * (B_A + 8 * wg + c), spin & 1);
                    uint32_t ok = TAGY;
#pragma unroll
                    for (int i = 0; i < 16; i++) ok &= lds32(sb + c * SLOT + wg * 8192 + (i >> 2) * 2048 + (i & 3) * 256 + (lane >> 4) * 1032 + (lane & 15) * 16);
                    if (__all_sync(~0u, ok)) break;
                    if (elect()) A_RETRY(c);
                    if (spin > SPIN) TRAP();
                }
                if (elect()) mbar_arrive(bars + 8 * (B_AR + 8 * wg + c));
            }
        }
        if (warp == 9) {
            const int f0 = slice_f0(jf), fbb = f0 + slice_na(jf);
            int slot = 8;
#pragma unroll 1
            for (int i = 0; i < 16; i++) {
                if (i >= 6) mbar_wait(bars + 8 * (B_DONE + i - 6));
                else if (i >= R_INFL) mbar_wait(bars + 8 * (B_FULL + 8 - R_INFL + i));
                if (elect()) {
                    mbar_expect(bars + 8 * (B_FULL + slot), 14336);
                    tma2d(sb + slot * SLOT, &p.w1 + (i & 1), f0, (i >> 1) * 64, bars + 8 * (B_FULL + slot));
                    tma2d(sb + slot * SLOT + 8192, &p.w1a + (i & 1), f0 + 64, (i >> 1) * 64, bars + 8 * (B_FULL + slot));
                }
                if (++slot == 14) slot = 8;
            }
#pragma unroll 1
            for (int i = 0; i < 8; i++) {
                mbar_wait(bars + 8 * (B_DONE + ((10 + i) & 15)), i >= 6);
                if (elect()) {
                    mbar_expect(bars + 8 * (B_FULL + slot), SLOT);
                    tma2d(sb + slot * SLOT, &p.w1, fbb, i * 64, bars + 8 * (B_FULL + slot));
                    tma2d(sb + slot * SLOT + 8192, &p.w3, fbb, i * 64, bars + 8 * (B_FULL + slot));
                }
                if (++slot == 14) slot = 8;
            }
            if (elect()) asm volatile("mbarrier.arrive.relaxed.cluster.shared::cluster.b64 _, [%0];" ::"r"(peer_sb + OFF_BAR + 8 * B_PEER) : "memory");
            const int fp0 = slice_f0(jf ^ 1), fpb = fp0 + slice_na(jf);
#pragma unroll 1
            for (int n = 0; n < 4; n++) {
                const int x = 256 * ke + 64 * (((jf >> 1) + 1 + n) & 3);
#pragma unroll
                for (int kind = 0; kind < 3; kind++) {
                    const int q = 3 * n + kind, ws = (int)(WS >> (4 * q)) & 15;
                    mbar_wait(bars + 8 * (B_DONE + ((q + 5) >> 1)), 1);
                    if (elect()) {
                        const uint32_t dst = sb + ws * SLOT, fb = bars + 8 * (B_FULL + ws);
                        mbar_expect(fb, kind == 2 ? SLOT : 14336);
                        if (kind < 2) tma2d(dst, &p.w2a, x, kind ? fp0 : f0, fb);
                        else { tma2d(dst, &p.w2b, x, fbb, fb); tma2d(dst + 8192, &p.w2b, x, fpb, fb); }
                    }
                }
            }
        } else if (warp == 11) {
            mbar_wait(bars + 8 * B_X1);
            if (lane == 0) { asm volatile("fence.release.gpu;" ::: "memory"); st_rlx32(q0.flag + 8 * b, tag); }
            __syncwarp();
#pragma unroll 1
            for (int spin = 0;; spin++) {
                if (__all_sync(~0u, ld_rlx32(q0.flag + 64 * grp + 8 * (lane & 7)) == tag)) break;
                if (spin > SPIN) TRAP();
            }
            asm volatile("fence.acquire.gpu;" ::: "memory");
            if (elect()) mbar_arrive(bars + 8 * B_PF);
        }
    } else {
        asm volatile("setmaxnreg.inc.sync.aligned.u32 232;");
        const int wg = warp >> 2, wt = tid & 127;
        const bool lead = wt == 0;
        int nretry = 0;
        __nv_bfloat16* const xo = p.out + xoff;

        const uint32_t dA = 64 + wg * 512 + (1u << 16), dB = 64 + (512u << 16);
        float ga[56], ua[56];
#define RING(i) (bars + 8 * (B_FULL + 8 + (i) % 6)), (((i) / 6) & 1)
        mbar_wait(RING(0));
#pragma unroll 1
        for (int spin = 0; spin < SPIN; spin++) {
            mbar_wait(bars + 8 * (B_A + 8 * wg), spin & 1);
            const uint32_t ta = sb + wg * 8192 + (warp & 3) * 2048 + (lane >> 4) * 1032 + (lane & 15) * 16;
            const uint32_t t0 = lds32(ta), t1 = lds32(ta + 256), t2 = lds32(ta + 512), t3 = lds32(ta + 768);
            wg_fence();
#pragma unroll
            for (int k = 0; k < 4; k++) wgmma_ss_n112(ga, dA + k * 2, dB + 8 * 1024 + k * 128, k);
            wg_commit();
            if (bar_and(4 + wg, 128, t0 & t1 & t2 & t3 & TAGY)) break;
            wg_wait<0>();
            bar_sync(4 + wg, 128);
            if (!(warp & 3) && elect()) A_RETRY(0);
            nretry++;
        }
        mbar_wait(RING(1));
        wg_fence();
#pragma unroll
        for (int k = 0; k < 4; k++) wgmma_ss_n112(ua, dA + k * 2, dB + 9 * 1024 + k * 128, k);
        wg_commit();
        {
            uint32_t slot = 10, par = 0;
#pragma unroll 1
            for (uint32_t c = 1; c < 8; c++) {
                mbar_wait2(bars + 8 * (B_FULL + slot), par, bars + 8 * (B_AR + 8 * wg + c), 0);
                wg_wait<1>();
                mbar_arrive_if(lead, bars + 8 * (B_DONE + 2 * c - 2));
                wg_fence();
#pragma unroll
                for (int k = 0; k < 4; k++) wgmma_ss_n112(ga, dA + c * 1024 + k * 2, dB + slot * 1024 + k * 128, 1);
                wg_commit();
                mbar_wait(bars + 8 * (B_FULL + slot + 1), par);
                wg_wait<1>();
                mbar_arrive_if(lead, bars + 8 * (B_DONE + 2 * c - 1));
                wg_fence();
#pragma unroll
                for (int k = 0; k < 4; k++) wgmma_ss_n112(ua, dA + c * 1024 + k * 2, dB + (slot + 1) * 1024 + k * 128, 1);
                wg_commit();
#pragma unroll
                for (int r = 0; r < 4; r++)
                    asm volatile("{\n.reg .pred p;\nsetp.eq.u32 p, %5, %6;\n@p st.global.v4.u32 [%0], {%1,%2,%3,%4};\n}\n" ::"l"(xo + ((r & 1) + 8 * (r >> 1)) * 65536),
                                 "r"(xr[r].x), "r"(xr[r].y), "r"(xr[r].z), "r"(xr[r].w), "r"(c), "r"(4 + r) : "memory");
                slot += 2;
                if (slot == 14) { slot = 8; par ^= 1; }
            }
        }
        wg_wait<1>();
        mbar_arrive_if(lead, bars + 8 * (B_DONE + 14));
        float pb[64];
        uint32_t hf[11][4], hp[11][4];
        const uint32_t inb = warp * 2048 + lane * 16;
#define H_SEND(i, off, bar) asm volatile("st.async.weak.shared::cluster.mbarrier::complete_tx::bytes.v4.b32 [%0], {%1,%2,%3,%4}, [%5];" \
            ::"r"(peer_sb + inb + (off)), "r"(hf[i][0]), "r"(hf[i][1]), "r"(hf[i][2]), "r"(hf[i][3]), "r"(peer_sb + OFF_BAR + 8 * ((bar) + warp)) : "memory")
#define H_RECV(i, off) do { const uint4 v_ = lds128(sb + inb + (off)); hp[i][0] = v_.x; hp[i][1] = v_.y; hp[i][2] = v_.z; hp[i][3] = v_.w; } while (0)
#pragma unroll
        for (int c = 0; c < 8; c++) {
            mbar_wait(bars + 8 * (B_FULL + 8 + (16 + c) % 6), ((16 + c) / 6) & 1);
            wg_fence();
#pragma unroll
            for (int k = 0; k < 4; k++) wgmma_ss_n128(pb, dA + c * 1024 + k * 2, dB + (8 + (16 + c) % 6) * 1024 + k * 128, c + k);
            wg_commit();
            if (c == 1 || c == 2) {
#pragma unroll
                for (int i = 4 * c - 4; i < 4 * c && i < 7; i++) {
#pragma unroll
                    for (int r = 0; r < 4; r++) {
                        uint32_t w = pack(silu_mul(ga[8 * i + 2 * r], ua[8 * i + 2 * r]), silu_mul(ga[8 * i + 2 * r + 1], ua[8 * i + 2 * r + 1]));
                        if (i == 6 && jf >= 6) w = 0;
                        asm volatile("" : "+r"(w));
                        hf[i][r] = w;
                    }
                }
            }
            if (c == 0) { __syncwarp(); mbar_arrive_if(lane == 0, bars + 8 * B_X1); }
            if (c == C_SEND) { mbar_wait(bars + 8 * B_PEER); H_SEND(0, 0, B_IN); H_SEND(1, 512, B_IN); H_SEND(2, 1024, B_IN); }
            if (c == C_SEND + 1) { H_SEND(3, 1536, B_IN); H_SEND(4, SLOT, B_IN); }
            if (c == C_SEND + 2) { H_SEND(5, SLOT + 512, B_IN); H_SEND(6, SLOT + 1024, B_IN); }
            wg_wait<1>();
            mbar_arrive_if(lead, bars + 8 * (B_DONE + ((15 + c) & 15)));
        }
        float a0[32], a1[32];
#define W_SLOT(q) ((int)((WS >> (4 * (q))) & 15))
#define W_WAIT(q) do { mbar_wait(bars + 8 * (B_FULL + W_SLOT(q)), (q) == 11); wg_fence(); } while (0)
#define MMA_A(acc, h, q, first, k0, k1) do { _Pragma("unroll") for (int k_ = k0; k_ < k1; k_++) wgmma_rs_n64(acc, h[k_], dB + W_SLOT(q) * 1024 + k_ * 128, !(first) || k_); } while (0)
#define EPI_B(i) do { _Pragma("unroll") for (int r = 0; r < 4; r++) \
            hf[7 + i][r] = pack(silu_mul(pb[8 * i + 2 * r], pb[32 + 8 * i + 2 * r]), silu_mul(pb[8 * i + 2 * r + 1], pb[32 + 8 * i + 2 * r + 1])); \
            H_SEND(7 + i, 2 * SLOT + i * 512, B_INB); } while (0)
#define MMA_B(acc, h, q, half, k0, k1) do { _Pragma("unroll") for (int k_ = k0; k_ < k1; k_++) wgmma_rs_n64(acc, h[7 + k_], dB + W_SLOT(q) * 1024 + (half) * 512 + k_ * 128, 1); } while (0)
        const uint32_t xa = sb + (16 * warp + (lane & 15)) * 128, xb = sb + (16 * warp + (lane >> 3)) * 128;
        __nv_bfloat16* const op = p.out + (uint32_t)(2 * warp * 128 + 8 * grp + (lane >> 3)) * 512 + 256 * ke + 8 * (lane & 7);
        uint32_t gq[8];
        uint4 ov[4];
#define O_GATE(n) do { _Pragma("unroll") for (int q_ = 0; q_ < 8; q_++) gq[q_] = lds32(sb + OFF_GB + (((jf >> 1) + 1 + (n)) & 3) * 128 + 4 * t + q_ * 16); } while (0)
#define O_STAGE(acc, q_) stsm4(xa + (((2 * q_ + (lane >> 4)) ^ (lane & 7)) << 4), \
            make_uint4(pack(acc[8 * q_] * blo(gq[2 * q_]), acc[8 * q_ + 1] * bhi(gq[2 * q_])), pack(acc[8 * q_ + 2] * blo(gq[2 * q_]), acc[8 * q_ + 3] * bhi(gq[2 * q_])), \
                       pack(acc[8 * q_ + 4] * blo(gq[2 * q_ + 1]), acc[8 * q_ + 5] * bhi(gq[2 * q_ + 1])), pack(acc[8 * q_ + 6] * blo(gq[2 * q_ + 1]), acc[8 * q_ + 7] * bhi(gq[2 * q_ + 1]))))
#define O_LOAD() do { __syncwarp(); _Pragma("unroll") for (int q_ = 0; q_ < 4; q_++) ov[q_] = lds128(xb + q_ * 512 + (((lane & 7) ^ (4 * (q_ & 1) + (lane >> 3))) << 4)); } while (0)
#define O_RED(n, q0, q1) do { _Pragma("unroll") for (int q_ = q0; q_ < q1; q_++) asm volatile("red.relaxed.gpu.global.add.noftz.v4.bf16x2 [%0], {%1,%2,%3,%4};" \
                ::"l"(op + (((jf >> 1) + 1 + (n)) & 3) * 64 + (q_ >> 1) * 65536 + (q_ & 1) * 2048), "r"(ov[q_].x), "r"(ov[q_].y), "r"(ov[q_].z), "r"(ov[q_].w) : "memory"); } while (0)
#define FA(acc, h, q, first, k0, k1) do { wg_fence(); MMA_A(acc, h, q, first, k0, k1); } while (0)
#define FB(acc, h, q, half, k0, k1) do { wg_fence(); MMA_B(acc, h, q, half, k0, k1); } while (0)
#define BLOCK(acc, prv, n) do { \
        O_GATE(n); W_WAIT(3 * n + 3); MMA_A(acc, hf, 3 * n + 3, 1, 0, 3); wg_commit(); wg_wait<1>(); \
        O_STAGE(prv, 0); O_STAGE(prv, 1); FA(acc, hf, 3 * n + 3, 1, 3, 5); O_STAGE(prv, 2); O_STAGE(prv, 3); O_LOAD(); FA(acc, hf, 3 * n + 3, 1, 5, 7); \
        W_WAIT(3 * n + 4); MMA_A(acc, hp, 3 * n + 4, 0, 0, 3); O_RED(n, 0, 2); W_WAIT(3 * n + 5); MMA_A(acc, hp, 3 * n + 4, 0, 3, 7); O_RED(n, 2, 4); \
        FB(acc, hf, 3 * n + 5, 0, 0, 4); FB(acc, hp, 3 * n + 5, 1, 0, 4); wg_commit(); } while (0)
        mbar_wait(bars + 8 * (B_IN + warp));
        W_WAIT(0); MMA_A(a0, hf, 0, 1, 0, NB); wg_commit();
        wg_wait<1>();
        mbar_arrive_if(lead, bars + 8 * (B_DONE + 7));
#pragma unroll
        for (int i = 0; i < 7; i++) H_RECV(i, (i >> 2) * SLOT + (i & 3) * 512);
        EPI_B(0);
        wg_fence(); MMA_A(a0, hf, 0, 1, NB, 7);
        EPI_B(1);
        W_WAIT(1); MMA_A(a0, hp, 1, 0, 0, 4);
        EPI_B(2);
        wg_fence(); MMA_A(a0, hp, 1, 0, 4, 7); wg_commit();
        EPI_B(3);
        W_WAIT(2); MMA_B(a0, hf, 2, 0, 0, 4); wg_commit();
        W_WAIT(3); MMA_A(a1, hf, 3, 1, 0, RB); wg_commit();
        wg_wait<2>();
        mbar_arrive_if(lead, bars + 8 * (B_DONE + 8));
        mbar_wait2(bars + 8 * (B_INB + warp), 0, bars + 8 * B_PF, 0);
#pragma unroll
        for (int i = 0; i < 4; i++) H_RECV(7 + i, 2 * SLOT + i * 512);
        O_GATE(0);
        FA(a1, hf, 3, 1, RB, 7);
        FB(a0, hp, 2, 1, 0, 4); wg_commit();
        W_WAIT(4); MMA_A(a1, hp, 4, 0, 0, 3); wg_commit();
        wg_wait<1>();
        O_STAGE(a0, 0); O_STAGE(a0, 1); FA(a1, hp, 4, 0, 3, 5); O_STAGE(a0, 2); O_STAGE(a0, 3); O_LOAD(); FA(a1, hp, 4, 0, 5, 7);
        W_WAIT(5); MMA_B(a1, hf, 5, 0, 0, 4); O_RED(0, 0, 2);
        W_WAIT(6); MMA_B(a1, hp, 5, 1, 0, 4); wg_commit(); O_RED(0, 2, 4);
        BLOCK(a0, a1, 1);
        BLOCK(a1, a0, 2);
        O_GATE(3);
        wg_wait<0>();
        O_STAGE(a1, 0); O_STAGE(a1, 1); O_STAGE(a1, 2); O_STAGE(a1, 3);
        O_LOAD();
        O_RED(3, 0, 4);
    }
}

typedef CUresult (*EncodeFn)(CUtensorMap*, CUtensorMapDataType, cuuint32_t, void*, const cuuint64_t*, const cuuint64_t*, const cuuint32_t*,
                             const cuuint32_t*, CUtensorMapInterleave, CUtensorMapSwizzle, CUtensorMapL2promotion, CUtensorMapFloatOOBfill);

static void make_map(EncodeFn enc, CUtensorMap* m, const void* ptr, int rank, cuuint64_t d0, cuuint64_t d1, cuuint64_t d2, cuuint64_t s1, cuuint64_t s2,
                     cuuint32_t b0, cuuint32_t b1, cuuint32_t b2, CUtensorMapSwizzle sw, CUtensorMapDataType dt = CU_TENSOR_MAP_DATA_TYPE_BFLOAT16) {
    cuuint64_t dims[3] = {d0, d1, d2}, strides[2] = {s1, s2};
    cuuint32_t box[3] = {b0, b1, b2}, es[3] = {1, 1, 1};
    enc(m, dt, rank, (void*)ptr, dims, strides, box, es, CU_TENSOR_MAP_INTERLEAVE_NONE, sw,
        CU_TENSOR_MAP_L2_PROMOTION_L2_128B, CU_TENSOR_MAP_FLOAT_OOB_FILL_NONE);
}

extern "C" void kernel_launch(void* const* d_in, const int* in_sizes, int n_in, void* d_out, int out_size) {
    (void)in_sizes; (void)n_in; (void)out_size;
    EncodeFn enc = nullptr;
    cudaDriverEntryPointQueryResult qr;
    cudaGetDriverEntryPoint("cuTensorMapEncodeTiled", (void**)&enc, cudaEnableDefault, &qr);
    cudaFuncSetAttribute(fused_kernel, cudaFuncAttributeMaxDynamicSharedMemorySize, SMEM_BYTES);
    Params p;
    Early q0;
    p.x = (const __nv_bfloat16*)d_in[0];
    p.wrp = (const __nv_bfloat16*)d_in[1];
    p.wip = (const __nv_bfloat16*)d_in[2];
    cudaGetSymbolAddress((void**)&p.E, g_E);
    cudaGetSymbolAddress((void**)&q0.X, g_X);
    cudaGetSymbolAddress((void**)&q0.mod, g_mod);
    cudaGetSymbolAddress((void**)&q0.flag, g_flag);
    cudaGetSymbolAddress((void**)&q0.tbl, g_tbl);
    p.w1p = (const __nv_bfloat16*)d_in[4];
    p.w3p = (const __nv_bfloat16*)d_in[5];
    p.w2p = (const __nv_bfloat16*)d_in[6];
    q0.c = (const __nv_bfloat16*)d_in[7];
    q0.wmod = (const __nv_bfloat16*)d_in[8];
    p.out = (__nv_bfloat16*)d_out;
    make_map(enc, &p.w1, d_in[4], 2, 1376, 512, 1, 2752, 0, 64, 64, 1, CU_TENSOR_MAP_SWIZZLE_128B);
    make_map(enc, &p.w3, d_in[5], 2, 1376, 512, 1, 2752, 0, 64, 64, 1, CU_TENSOR_MAP_SWIZZLE_128B);
    make_map(enc, &p.w1a, d_in[4], 2, 1376, 512, 1, 2752, 0, 48, 64, 1, CU_TENSOR_MAP_SWIZZLE_128B);
    make_map(enc, &p.w3a, d_in[5], 2, 1376, 512, 1, 2752, 0, 48, 64, 1, CU_TENSOR_MAP_SWIZZLE_128B);
    make_map(enc, &p.w2a, d_in[6], 2, 512, 1376, 1, 1024, 0, 64, 112, 1, CU_TENSOR_MAP_SWIZZLE_128B);
    make_map(enc, &p.w2b, d_in[6], 2, 512, 1376, 1, 1024, 0, 64, 64, 1, CU_TENSOR_MAP_SWIZZLE_128B);
    make_map(enc, &p.wr, p.wrp, 3, 4112, 8, 16, 16 * 8224, 8224, 40, 8, 16, CU_TENSOR_MAP_SWIZZLE_NONE);
    make_map(enc, &p.wi, p.wip, 3, 4112, 8, 16, 16 * 8224, 8224, 40, 8, 16, CU_TENSOR_MAP_SWIZZLE_NONE);
    make_map(enc, &p.wrs, p.wrp, 2, 4112, 128, 1, 8224, 0, 8, 128, 1, CU_TENSOR_MAP_SWIZZLE_NONE);
    make_map(enc, &p.wis, p.wip, 2, 4112, 128, 1, 8224, 0, 8, 128, 1, CU_TENSOR_MAP_SWIZZLE_NONE);
    {
        cuuint64_t dims[4] = {64, 16, 8, 128}, strides[3] = {131072, 128, 1024};
        cuuint32_t box[4] = {64, 16, 8, 1}, es[4] = {1, 1, 1, 1};
        enc(&p.xin, CU_TENSOR_MAP_DATA_TYPE_BFLOAT16, 4, (void*)p.x, dims, strides, box, es, CU_TENSOR_MAP_INTERLEAVE_NONE, CU_TENSOR_MAP_SWIZZLE_128B,
            CU_TENSOR_MAP_L2_PROMOTION_L2_128B, CU_TENSOR_MAP_FLOAT_OOB_FILL_NONE);
    }
    make_map(enc, &p.ea, p.E, 2, 4096, 128, 1, 16384, 0, 256, 4, 1, CU_TENSOR_MAP_SWIZZLE_NONE, CU_TENSOR_MAP_DATA_TYPE_UINT32);
    fused_kernel<<<128, 384, SMEM_BYTES, cudaStreamPerThread>>>(q0, p);
}
```
